```python
import torch

def _softmax(x, axis=-1):
    return torch.softmax(x, dim=axis)
def _gelu(x):
    return torch.nn.functional.gelu(x, approximate="tanh")
def _silu(x):
    return torch.nn.functional.silu(x)
def _sigmoid(x):
    return torch.sigmoid(x)
def _layernorm(x, axis=-1, eps=1e-5):
    m = x.mean(dim=axis, keepdim=True)
    v = x.var(dim=axis, keepdim=True, unbiased=False)
    return (x - m) / torch.sqrt(v + eps)
def _scatter_add(tgt, idx, src, axis=0):
    return tgt.clone().index_add_(axis, idx, src)
def _segment_sum(src, seg, n):
    out = torch.zeros((n,) + src.shape[1:], dtype=src.dtype)
    return out.index_add_(0, seg, src)
def _pad(x, pw):
    flat = tuple(v for pair in reversed(pw) for v in pair)
    return torch.nn.functional.pad(x, flat)

kernel_name = 'interleave_layers__sliding_local_dilated__swiglu_ffn__prompt'

def setup_inputs():

    _w = (lambda a: (lambda t: t.to(torch.bfloat16) if t.is_floating_point() else t)(torch.as_tensor(a)))
    def _A_setup():
        B, S, D = 1, 2048, 1024
        return {
            "x": _w((lambda *s: torch.randn(*s, dtype=torch.bfloat16) * 0.05)(B, S, D)),
            "wqkv": _w((lambda *s: torch.randn(*s, dtype=torch.bfloat16) * 0.05)(D, 3 * D)),
            "wo": _w((lambda *s: torch.randn(*s, dtype=torch.bfloat16) * 0.05)(D, D)),
        }
    _A_in = _A_setup()

    def _B_setup():
        B, S, D, F = 1, 2048, 1024, 3584
        return {
            "x": _w((lambda *s: torch.randn(*s, dtype=torch.bfloat16) * 0.05)(B, S, D)),
            "w_gate": _w((lambda *s: torch.randn(*s, dtype=torch.bfloat16) * 0.05)(D, F)),
            "w_up": _w((lambda *s: torch.randn(*s, dtype=torch.bfloat16) * 0.05)(D, F)),
            "w_down": _w((lambda *s: torch.randn(*s, dtype=torch.bfloat16) * 0.05)(F, D)),
        }
    _B_in = _B_setup()

    return {
        "A_x": _A_in["x"],
        "A_wqkv": _A_in["wqkv"],
        "A_wo": _A_in["wo"],
        "B_x": _B_in["x"],
        "B_w_gate": _B_in["w_gate"],
        "B_w_up": _B_in["w_up"],
        "B_w_down": _B_in["w_down"],
    }

def reference(A_x, A_wqkv, A_wo, B_x, B_w_gate, B_w_up, B_w_down):
    def _A_ref(x, wqkv, wo):
        B, S, D = x.shape
        H = 32; Dh = D // H
        W, dil = 8, 2
        qkv = (lambda x, *d: x.permute(*d))((x @ wqkv).reshape(B, S, 3, H, Dh), 2, 0, 3, 1, 4)
        q, k, v = qkv[0], qkv[1], qkv[2]
        scale = Dh ** -0.5
        pos = torch.arange(S)
        off = torch.arange(W) * dil
        idx = pos[:, None] - off[None, :]
        mask = idx >= 0
        idx_c = torch.where(mask, idx, 0).reshape(-1)
        kg = k[:, :, idx_c, :].reshape(B, H, S, W, Dh)
        vg = v[:, :, idx_c, :].reshape(B, H, S, W, Dh)
        logits = torch.einsum("bhsd,bhswd->bhsw", q, kg) * scale
        logits = torch.where(mask[None, None, :, :], logits, -1e9)
        attn = _softmax(logits, axis=-1)
        o = torch.einsum("bhsw,bhswd->bhsd", attn, vg)
        return (lambda x, *d: x.permute(*d))(o, 0, 2, 1, 3).reshape(B, S, D) @ wo

    def _B_ref(x, w_gate, w_up, w_down):
        g = _silu(x @ w_gate)
        u = x @ w_up
        return (g * u) @ w_down

    x = A_x
    x = x + _A_ref(_layernorm(x, axis=-1), A_wqkv, A_wo)
    x = x + _B_ref(_layernorm(x, axis=-1), B_w_gate, B_w_up, B_w_down)
    x = x + _A_ref(_layernorm(x, axis=-1), A_wqkv, A_wo)
    x = x + _B_ref(_layernorm(x, axis=-1), B_w_gate, B_w_up, B_w_down)
    return x
```

```cpp
#include <cuda_runtime.h>
#include <cuda_bf16.h>
#include <cuda.h>
#include <stdint.h>

namespace {

constexpr int SEQ = 2048, DM = 1024, FF = 3584;
constexpr int NCTA = 128;
constexpr uint32_t CAP = 196608;
constexpr uint32_t KV_OFF = 163840;
constexpr uint32_t KV_WG = 14848;
constexpr uint32_t KV_K = 9216, KV_R = 14336;
constexpr uint32_t STG_OFF = CAP;
constexpr uint32_t MISC_OFF = CAP + 32768;
constexpr uint32_t CSQ_OFF = MISC_OFF + 384;
constexpr uint32_t CSG_OFF = CSQ_OFF + 1536;
constexpr uint32_t SMEM_BYTES = CSG_OFF + 512 + 16;
constexpr int NSPARE = 4;

constexpr uint32_t B_EMPTY = 0, B_FULL = 64, B_DONE = 128  , B_HGO = 144  , B_HALO = 160  , B_CSQ = 176  ,
                   B_CS = 192, B_CSFREE = 200, B_XL = 216, B_BOX1 = 224, M_TAG = CSG_OFF + 512 - MISC_OFF,
                   B_SLAB = 256  , B_SFULL = 256, B_SEMPTY = 320;

enum { F_NONE = 0, F_O0, F_O1, F_X1, F_X1B, F_H0, F_H1, F_X0, F_X0B, F_COUNT };
constexpr int NCS = 3 * DM + 2 * FF;

struct Scratch {
  uint4 flags[16 * 8];
  uint32_t epoch[256];
  float2 stats[8 * SEQ];
  uint4 part[8 * NCS / 4];
  uint4 halo[4 * 16 * 8 * 2 * 5 * 32];
  __nv_bfloat16 x[SEQ * DM], o[SEQ * DM], h[SEQ * FF];
};
__device__ __align__(1024) Scratch g_s;

constexpr int NSEG = 23, NST = 168;
struct Tabs { uint32_t seg[2 * NSEG + 2], seq[9][8], ring[2 * NST + 2]; };
struct Params {
  Scratch* s;
  __nv_bfloat16* out;
  int by_sm;
  Tabs t;
  CUtensorMap x0, x, o, h, wqkv, wo, wg, wu, wd;
};

__device__ __forceinline__ uint32_t smem_u32(const void* p) { return (uint32_t)__cvta_generic_to_shared(p); }
__device__ __forceinline__ void mbar_init(uint32_t bar, uint32_t cnt) {
  asm volatile("mbarrier.init.shared::cta.b64 [%0], %1;" ::"r"(bar), "r"(cnt));
}
__device__ __forceinline__ void mbar_expect_tx(uint32_t bar, uint32_t bytes) {
  asm volatile("mbarrier.arrive.expect_tx.shared::cta.b64 _, [%0], %1;" ::"r"(bar), "r"(bytes) : "memory");
}
__device__ __forceinline__ void mbar_arrive(uint32_t bar) {
  asm volatile("mbarrier.arrive.shared::cta.b64 _, [%0];" ::"r"(bar) : "memory");
}
__device__ __forceinline__ bool mbar_try(uint32_t bar, uint32_t parity) {
  uint32_t ok;
  asm volatile("{\n.reg .pred p;\nmbarrier.try_wait.parity.shared::cta.b64 p, [%1], %2;\nselp.u32 %0, 1, 0, p;\n}"
               : "=r"(ok) : "r"(bar), "r"(parity) : "memory");
  return ok;
}
__device__ __forceinline__ void mbar_wait(uint32_t bar, uint32_t parity) {
  uint32_t n = 0;
  while (!mbar_try(bar, parity)) {
    if (++n > (1u << 20)) __trap();
  }
}
__device__ __forceinline__ void mbar_wait_idle(uint32_t bar, uint32_t parity) {
  uint32_t n = 0, ok;
  do {
    asm volatile("{\n.reg .pred p;\nmbarrier.try_wait.parity.shared::cta.b64 p, [%1], %2, %3;\nselp.u32 %0, 1, 0, p;\n}"
                 : "=r"(ok) : "r"(bar), "r"(parity), "n"(20000) : "memory");
    if (++n > (1u << 16)) __trap();
  } while (!ok);
}
__device__ __forceinline__ void tma_load(uint32_t dst, const void* tm, uint32_t bar, int c0, int c1) {
  asm volatile("cp.async.bulk.tensor.2d.shared::cluster.global.mbarrier::complete_tx::bytes [%0], [%1, {%3, %4}], [%2];"
               ::"r"(dst), "l"(tm), "r"(bar), "r"(c0), "r"(c1) : "memory");
}
__device__ __forceinline__ void tma_load3(uint32_t dst, const void* tm, uint32_t bar, int c0, int c1) {
  asm volatile("cp.async.bulk.tensor.3d.shared::cluster.global.mbarrier::complete_tx::bytes [%0], [%1, {%3, %4, %5}], [%2];"
               ::"r"(dst), "l"(tm), "r"(bar), "r"(c0), "r"(c1), "r"(0) : "memory");
}
__device__ __forceinline__ void tma_store3(const void* tm, uint32_t src, int c0, int c1) {
  asm volatile("cp.async.bulk.tensor.3d.global.shared::cta.bulk_group [%0, {%2, %3, %4}], [%1];\n"
               "cp.async.bulk.commit_group;\ncp.async.bulk.wait_group 0;" ::"l"(tm), "r"(src), "r"(c0), "r"(c1), "r"(0) : "memory");
}
__device__ __forceinline__ void tma_load_mc(uint32_t dst, const void* tm, uint32_t bar, int c0, int c1) {
  asm volatile("cp.async.bulk.tensor.2d.shared::cluster.global.mbarrier::complete_tx::bytes.multicast::cluster [%0], [%1, {%3, %4}], [%2], %5;"
               ::"r"(dst), "l"(tm), "r"(bar), "r"(c0), "r"(c1), "h"((uint16_t)3) : "memory");
}
__device__ __forceinline__ void tma_load5_mc(uint32_t dst, const void* tm, uint32_t bar, int c0, int c4) {
  asm volatile("cp.async.bulk.tensor.5d.shared::cluster.global.mbarrier::complete_tx::bytes.multicast::cluster [%0], [%1, {%3, %6, %6, %6, %4}], [%2], %5;"
               ::"r"(dst), "l"(tm), "r"(bar), "r"(c0), "r"(c4), "h"((uint16_t)3), "r"(0) : "memory");
}
__device__ __forceinline__ void fence_proxy_async() { asm volatile("fence.proxy.async.global;" ::: "memory"); }
__device__ __forceinline__ void st_tag(uint4* p, uint32_t a, uint32_t b, uint32_t c, uint32_t tag) {
  asm volatile("{\n.reg .b128 t;\n.reg .b64 lo, hi;\nmov.b64 lo, {%1, %2};\nmov.b64 hi, {%3, %4};\nmov.b128 t, {lo, hi};\n"
               "st.relaxed.gpu.global.b128 [%0], t;\n}" ::"l"(p), "r"(a), "r"(b), "r"(c), "r"(tag) : "memory");
}
__device__ __forceinline__ void st_tag_if(bool on, uint4* p, uint32_t a, uint32_t b, uint32_t c, uint32_t tag) {
  asm volatile("{\n.reg .b128 t;\n.reg .b64 lo, hi;\n.reg .pred p;\nsetp.ne.u32 p, %5, 0;\nmov.b64 lo, {%1, %2};\nmov.b64 hi, {%3, %4};\nmov.b128 t, {lo, hi};\n"
               "@p st.relaxed.gpu.global.b128 [%0], t;\n}" ::"l"(p), "r"(a), "r"(b), "r"(c), "r"(tag), "r"((uint32_t)on) : "memory");
}
__device__ __forceinline__ uint4 ld_tag(const uint4* p) {
  uint4 v;
  asm volatile("{\n.reg .b128 t;\n.reg .b64 lo, hi;\nld.relaxed.gpu.global.b128 t, [%4];\nmov.b128 {lo, hi}, t;\n"
               "mov.b64 {%0, %1}, lo;\nmov.b64 {%2, %3}, hi;\n}" : "=r"(v.x), "=r"(v.y), "=r"(v.z), "=r"(v.w) : "l"(p) : "memory");
  return v;
}
__device__ __forceinline__ float tanh_approx(float x) { float y; asm("tanh.approx.f32 %0, %1;" : "=f"(y) : "f"(x)); return y; }
__device__ __forceinline__ void fence_proxy_async_smem() { asm volatile("fence.proxy.async.shared::cta;" ::: "memory"); }
__device__ __forceinline__ void fence_gpu() { asm volatile("fence.release.gpu;" ::: "memory"); }
__device__ __forceinline__ uint32_t ld_epoch(const Params& p) {
  uint32_t e;
  asm volatile("ld.relaxed.gpu.global.u32 %0, [%1];" : "=r"(e) : "l"(p.s->epoch + blockIdx.x) : "memory");
  return e;
}
__device__ __forceinline__ void st_flag(void* p, uint32_t v) {
  asm volatile("st.relaxed.gpu.global.u8 [%0], %1;" ::"l"(p), "r"(v) : "memory");
}
__device__ __forceinline__ uint32_t ld_flag(const void* p) {
  uint32_t v;
  asm volatile("ld.relaxed.gpu.global.u8 %0, [%1];" : "=r"(v) : "l"(p) : "memory");
  return v;
}
__device__ __forceinline__ void wgmma_fence() { asm volatile("wgmma.fence.sync.aligned;" ::: "memory"); }
__device__ __forceinline__ void wgmma_commit() { asm volatile("wgmma.commit_group.sync.aligned;" ::: "memory"); }
template <int N> __device__ __forceinline__ void wgmma_wait() {
  asm volatile("wgmma.wait_group.sync.aligned %0;" ::"n"(N) : "memory");
}
__device__ __forceinline__ void cluster_arrive() { asm volatile("barrier.cluster.arrive.relaxed;" ::: "memory"); }
__device__ __forceinline__ void cluster_wait() { asm volatile("barrier.cluster.wait;" ::: "memory"); }
__device__ __forceinline__ void bar_sync(int id, int n) { asm volatile("bar.sync %0, %1;" ::"r"(id), "r"(n) : "memory"); }
__device__ __forceinline__ uint32_t pack_bf16(float lo, float hi) {
  uint32_t r;
  asm("cvt.rn.bf16x2.f32 %0, %1, %2;" : "=r"(r) : "f"(hi), "f"(lo));
  return r;
}
__device__ __forceinline__ float bf_lo(uint32_t v) { return __uint_as_float(v << 16); }
__device__ __forceinline__ float bf_hi(uint32_t v) { return __uint_as_float(v & 0xffff0000u); }
__device__ __forceinline__ void stsm4(uint32_t a, uint32_t r0, uint32_t r1, uint32_t r2, uint32_t r3) {
  asm volatile("stmatrix.sync.aligned.m8n8.x4.shared.b16 [%0], {%1, %2, %3, %4};" ::"r"(a), "r"(r0), "r"(r1), "r"(r2), "r"(r3) : "memory");
}
__device__ __forceinline__ void ldsm4(uint32_t a, uint32_t& r0, uint32_t& r1, uint32_t& r2, uint32_t& r3) {
  asm volatile("ldmatrix.sync.aligned.m8n8.x4.shared.b16 {%0, %1, %2, %3}, [%4];" : "=r"(r0), "=r"(r1), "=r"(r2), "=r"(r3) : "r"(a) : "memory");
}
__device__ __forceinline__ void ldsm4t(uint32_t a, uint32_t& r0, uint32_t& r1, uint32_t& r2, uint32_t& r3) {
  asm volatile("ldmatrix.sync.aligned.m8n8.x4.trans.shared.b16 {%0, %1, %2, %3}, [%4];" : "=r"(r0), "=r"(r1), "=r"(r2), "=r"(r3) : "r"(a) : "memory");
}
__device__ __forceinline__ void mma16816(float (&c)[4], uint32_t a0, uint32_t a1, uint32_t a2, uint32_t a3, uint32_t b0, uint32_t b1) {
  asm volatile("mma.sync.aligned.m16n8k16.row.col.f32.bf16.bf16.f32 {%0,%1,%2,%3}, {%4,%5,%6,%7}, {%8,%9}, {%0,%1,%2,%3};"
               : "+f"(c[0]), "+f"(c[1]), "+f"(c[2]), "+f"(c[3]) : "r"(a0), "r"(a1), "r"(a2), "r"(a3), "r"(b0), "r"(b1));
}
__device__ __forceinline__ float ex2(float x) { float y; asm("ex2.approx.ftz.f32 %0, %1;" : "=f"(y) : "f"(x)); return y; }
__device__ __forceinline__ float rcp(float x) { float y; asm("rcp.approx.ftz.f32 %0, %1;" : "=f"(y) : "f"(x)); return y; }
__device__ __forceinline__ uint32_t pin(uint32_t a) {
  uint32_t r;
  asm volatile("mov.u32 %0, %1;" : "=r"(r) : "r"(a) : "memory");
  return r;
}
__device__ __forceinline__ float lds32f(uint32_t a) {
  float v;
  asm volatile("ld.shared.f32 %0, [%1];" : "=f"(v) : "r"(a) : "memory");
  return v;
}
__device__ __forceinline__ void sts32f(uint32_t a, float v) { asm volatile("st.shared.f32 [%0], %1;" ::"r"(a), "f"(v) : "memory"); }
__device__ __forceinline__ void sts64f(uint32_t a, float x, float y) { asm volatile("st.shared.v2.f32 [%0], {%1, %2};" ::"r"(a), "f"(x), "f"(y) : "memory"); }
__device__ __forceinline__ float2 ld_b64(const void* p) {
  float2 v;
  asm volatile("{\n.reg .b64 t;\nld.relaxed.gpu.global.b64 t, [%2];\nmov.b64 {%0, %1}, t;\n}" : "=f"(v.x), "=f"(v.y) : "l"(p) : "memory");
  return v;
}
__device__ __forceinline__ void st_b64(void* p, uint32_t x, uint32_t y) {
  asm volatile("{\n.reg .b64 t;\nmov.b64 t, {%1, %2};\nst.relaxed.gpu.global.b64 [%0], t;\n}" ::"l"(p), "r"(x), "r"(y) : "memory");
}
__device__ __forceinline__ uint4 lds128(uint32_t a) {
  uint4 v;
  asm volatile("ld.shared.v4.u32 {%0, %1, %2, %3}, [%4];" : "=r"(v.x), "=r"(v.y), "=r"(v.z), "=r"(v.w) : "r"(a) : "memory");
  return v;
}
__device__ __forceinline__ float qsum(float v) {
  v += __shfl_xor_sync(0xffffffffu, v, 1);
  v += __shfl_xor_sync(0xffffffffu, v, 2);
  return v;
}
__device__ __forceinline__ void sts128(uint32_t a, uint32_t x, uint32_t y, uint32_t z, uint32_t w) {
  asm volatile("st.shared.v4.u32 [%0], {%1, %2, %3, %4};" ::"r"(a), "r"(x), "r"(y), "r"(z), "r"(w) : "memory");
}
__device__ __forceinline__ float4 lds128f(uint32_t a) {
  float4 v;
  asm volatile("ld.shared.v4.f32 {%0, %1, %2, %3}, [%4];" : "=f"(v.x), "=f"(v.y), "=f"(v.z), "=f"(v.w) : "r"(a) : "memory");
  return v;
}
__device__ __forceinline__ void stg128(void* p, uint32_t x, uint32_t y, uint32_t z, uint32_t w) {
  asm volatile("st.global.v4.u32 [%0], {%1, %2, %3, %4};" ::"l"(p), "r"(x), "r"(y), "r"(z), "r"(w) : "memory");
}
__device__ __forceinline__ void mma1688z(float (&c)[4], uint32_t a0, uint32_t b0) {
  asm volatile("mma.sync.aligned.m16n8k8.row.col.f32.bf16.bf16.f32 {%0,%1,%2,%3}, {%4,%5}, {%6}, {%7,%7,%7,%7};"
               : "=f"(c[0]), "=f"(c[1]), "=f"(c[2]), "=f"(c[3]) : "r"(a0), "r"(0u), "r"(b0), "f"(0.f));
}
__device__ __forceinline__ void mma16816z(float (&c)[4], uint32_t a0, uint32_t a1, uint32_t a2, uint32_t a3, uint32_t b0, uint32_t b1) {
  asm volatile("mma.sync.aligned.m16n8k16.row.col.f32.bf16.bf16.f32 {%0,%1,%2,%3}, {%4,%5,%6,%7}, {%8,%9}, {%10,%10,%10,%10};"
               : "=f"(c[0]), "=f"(c[1]), "=f"(c[2]), "=f"(c[3]) : "r"(a0), "r"(a1), "r"(a2), "r"(a3), "r"(b0), "r"(b1), "f"(0.f));
}

__device__ __forceinline__ void wgmma_n128(float (&d0)[64], uint64_t da, uint64_t db) {
  asm volatile(
    "wgmma.mma_async.sync.aligned.m64n128k16.f32.bf16.bf16 "
    "{%0,%1,%2,%3,%4,%5,%6,%7,%8,%9,%10,%11,%12,%13,%14,%15,"
    "%16,%17,%18,%19,%20,%21,%22,%23,%24,%25,%26,%27,%28,%29,%30,%31,"
    "%32,%33,%34,%35,%36,%37,%38,%39,%40,%41,%42,%43,%44,%45,%46,%47,"
    "%48,%49,%50,%51,%52,%53,%54,%55,%56,%57,%58,%59,%60,%61,%62,%63},"
    " %64, %65, 1, 1, 1, 0, 1;"
    : "+f"(d0[0]), "+f"(d0[1]), "+f"(d0[2]), "+f"(d0[3]), "+f"(d0[4]), "+f"(d0[5]), "+f"(d0[6]), "+f"(d0[7]),
      "+f"(d0[8]), "+f"(d0[9]), "+f"(d0[10]), "+f"(d0[11]), "+f"(d0[12]), "+f"(d0[13]), "+f"(d0[14]), "+f"(d0[15]),
      "+f"(d0[16]), "+f"(d0[17]), "+f"(d0[18]), "+f"(d0[19]), "+f"(d0[20]), "+f"(d0[21]), "+f"(d0[22]), "+f"(d0[23]),
      "+f"(d0[24]), "+f"(d0[25]), "+f"(d0[26]), "+f"(d0[27]), "+f"(d0[28]), "+f"(d0[29]), "+f"(d0[30]), "+f"(d0[31]),
      "+f"(d0[32]), "+f"(d0[33]), "+f"(d0[34]), "+f"(d0[35]), "+f"(d0[36]), "+f"(d0[37]), "+f"(d0[38]), "+f"(d0[39]),
      "+f"(d0[40]), "+f"(d0[41]), "+f"(d0[42]), "+f"(d0[43]), "+f"(d0[44]), "+f"(d0[45]), "+f"(d0[46]), "+f"(d0[47]),
      "+f"(d0[48]), "+f"(d0[49]), "+f"(d0[50]), "+f"(d0[51]), "+f"(d0[52]), "+f"(d0[53]), "+f"(d0[54]), "+f"(d0[55]),
      "+f"(d0[56]), "+f"(d0[57]), "+f"(d0[58]), "+f"(d0[59]), "+f"(d0[60]), "+f"(d0[61]), "+f"(d0[62]), "+f"(d0[63])
    : "l"(da), "l"(db));
}
__device__ __forceinline__ void wgmma_n128_init(float (&d0)[64], uint64_t da, uint64_t db) {
  asm volatile(
    "wgmma.mma_async.sync.aligned.m64n128k16.f32.bf16.bf16 "
    "{%0,%1,%2,%3,%4,%5,%6,%7,%8,%9,%10,%11,%12,%13,%14,%15,"
    "%16,%17,%18,%19,%20,%21,%22,%23,%24,%25,%26,%27,%28,%29,%30,%31,"
    "%32,%33,%34,%35,%36,%37,%38,%39,%40,%41,%42,%43,%44,%45,%46,%47,"
    "%48,%49,%50,%51,%52,%53,%54,%55,%56,%57,%58,%59,%60,%61,%62,%63},"
    " %64, %65, 0, 1, 1, 0, 1;"
    : "=f"(d0[0]), "=f"(d0[1]), "=f"(d0[2]), "=f"(d0[3]), "=f"(d0[4]), "=f"(d0[5]), "=f"(d0[6]), "=f"(d0[7]),
      "=f"(d0[8]), "=f"(d0[9]), "=f"(d0[10]), "=f"(d0[11]), "=f"(d0[12]), "=f"(d0[13]), "=f"(d0[14]), "=f"(d0[15]),
      "=f"(d0[16]), "=f"(d0[17]), "=f"(d0[18]), "=f"(d0[19]), "=f"(d0[20]), "=f"(d0[21]), "=f"(d0[22]), "=f"(d0[23]),
      "=f"(d0[24]), "=f"(d0[25]), "=f"(d0[26]), "=f"(d0[27]), "=f"(d0[28]), "=f"(d0[29]), "=f"(d0[30]), "=f"(d0[31]),
      "=f"(d0[32]), "=f"(d0[33]), "=f"(d0[34]), "=f"(d0[35]), "=f"(d0[36]), "=f"(d0[37]), "=f"(d0[38]), "=f"(d0[39]),
      "=f"(d0[40]), "=f"(d0[41]), "=f"(d0[42]), "=f"(d0[43]), "=f"(d0[44]), "=f"(d0[45]), "=f"(d0[46]), "=f"(d0[47]),
      "=f"(d0[48]), "=f"(d0[49]), "=f"(d0[50]), "=f"(d0[51]), "=f"(d0[52]), "=f"(d0[53]), "=f"(d0[54]), "=f"(d0[55]),
      "=f"(d0[56]), "=f"(d0[57]), "=f"(d0[58]), "=f"(d0[59]), "=f"(d0[60]), "=f"(d0[61]), "=f"(d0[62]), "=f"(d0[63])
    : "l"(da), "l"(db));
}
__device__ __forceinline__ void wgmma_n192(float (&d0)[96], uint64_t da, uint64_t db) {
  asm volatile(
    "wgmma.mma_async.sync.aligned.m64n192k16.f32.bf16.bf16 "
    "{%0,%1,%2,%3,%4,%5,%6,%7,%8,%9,%10,%11,%12,%13,%14,%15,"
    "%16,%17,%18,%19,%20,%21,%22,%23,%24,%25,%26,%27,%28,%29,%30,%31,"
    "%32,%33,%34,%35,%36,%37,%38,%39,%40,%41,%42,%43,%44,%45,%46,%47,"
    "%48,%49,%50,%51,%52,%53,%54,%55,%56,%57,%58,%59,%60,%61,%62,%63,"
    "%64,%65,%66,%67,%68,%69,%70,%71,%72,%73,%74,%75,%76,%77,%78,%79,"
    "%80,%81,%82,%83,%84,%85,%86,%87,%88,%89,%90,%91,%92,%93,%94,%95},"
    " %96, %97, 1, 1, 1, 0, 1;"
    : "+f"(d0[0]), "+f"(d0[1]), "+f"(d0[2]), "+f"(d0[3]), "+f"(d0[4]), "+f"(d0[5]), "+f"(d0[6]), "+f"(d0[7]),
      "+f"(d0[8]), "+f"(d0[9]), "+f"(d0[10]), "+f"(d0[11]), "+f"(d0[12]), "+f"(d0[13]), "+f"(d0[14]), "+f"(d0[15]),
      "+f"(d0[16]), "+f"(d0[17]), "+f"(d0[18]), "+f"(d0[19]), "+f"(d0[20]), "+f"(d0[21]), "+f"(d0[22]), "+f"(d0[23]),
      "+f"(d0[24]), "+f"(d0[25]), "+f"(d0[26]), "+f"(d0[27]), "+f"(d0[28]), "+f"(d0[29]), "+f"(d0[30]), "+f"(d0[31]),
      "+f"(d0[32]), "+f"(d0[33]), "+f"(d0[34]), "+f"(d0[35]), "+f"(d0[36]), "+f"(d0[37]), "+f"(d0[38]), "+f"(d0[39]),
      "+f"(d0[40]), "+f"(d0[41]), "+f"(d0[42]), "+f"(d0[43]), "+f"(d0[44]), "+f"(d0[45]), "+f"(d0[46]), "+f"(d0[47]),
      "+f"(d0[48]), "+f"(d0[49]), "+f"(d0[50]), "+f"(d0[51]), "+f"(d0[52]), "+f"(d0[53]), "+f"(d0[54]), "+f"(d0[55]),
      "+f"(d0[56]), "+f"(d0[57]), "+f"(d0[58]), "+f"(d0[59]), "+f"(d0[60]), "+f"(d0[61]), "+f"(d0[62]), "+f"(d0[63]),
      "+f"(d0[64]), "+f"(d0[65]), "+f"(d0[66]), "+f"(d0[67]), "+f"(d0[68]), "+f"(d0[69]), "+f"(d0[70]), "+f"(d0[71]),
      "+f"(d0[72]), "+f"(d0[73]), "+f"(d0[74]), "+f"(d0[75]), "+f"(d0[76]), "+f"(d0[77]), "+f"(d0[78]), "+f"(d0[79]),
      "+f"(d0[80]), "+f"(d0[81]), "+f"(d0[82]), "+f"(d0[83]), "+f"(d0[84]), "+f"(d0[85]), "+f"(d0[86]), "+f"(d0[87]),
      "+f"(d0[88]), "+f"(d0[89]), "+f"(d0[90]), "+f"(d0[91]), "+f"(d0[92]), "+f"(d0[93]), "+f"(d0[94]), "+f"(d0[95])
    : "l"(da), "l"(db));
}
__device__ __forceinline__ void wgmma_n192_init(float (&d0)[96], uint64_t da, uint64_t db) {
  asm volatile(
    "wgmma.mma_async.sync.aligned.m64n192k16.f32.bf16.bf16 "
    "{%0,%1,%2,%3,%4,%5,%6,%7,%8,%9,%10,%11,%12,%13,%14,%15,"
    "%16,%17,%18,%19,%20,%21,%22,%23,%24,%25,%26,%27,%28,%29,%30,%31,"
    "%32,%33,%34,%35,%36,%37,%38,%39,%40,%41,%42,%43,%44,%45,%46,%47,"
    "%48,%49,%50,%51,%52,%53,%54,%55,%56,%57,%58,%59,%60,%61,%62,%63,"
    "%64,%65,%66,%67,%68,%69,%70,%71,%72,%73,%74,%75,%76,%77,%78,%79,"
    "%80,%81,%82,%83,%84,%85,%86,%87,%88,%89,%90,%91,%92,%93,%94,%95},"
    " %96, %97, 0, 1, 1, 0, 1;"
    : "=f"(d0[0]), "=f"(d0[1]), "=f"(d0[2]), "=f"(d0[3]), "=f"(d0[4]), "=f"(d0[5]), "=f"(d0[6]), "=f"(d0[7]),
      "=f"(d0[8]), "=f"(d0[9]), "=f"(d0[10]), "=f"(d0[11]), "=f"(d0[12]), "=f"(d0[13]), "=f"(d0[14]), "=f"(d0[15]),
      "=f"(d0[16]), "=f"(d0[17]), "=f"(d0[18]), "=f"(d0[19]), "=f"(d0[20]), "=f"(d0[21]), "=f"(d0[22]), "=f"(d0[23]),
      "=f"(d0[24]), "=f"(d0[25]), "=f"(d0[26]), "=f"(d0[27]), "=f"(d0[28]), "=f"(d0[29]), "=f"(d0[30]), "=f"(d0[31]),
      "=f"(d0[32]), "=f"(d0[33]), "=f"(d0[34]), "=f"(d0[35]), "=f"(d0[36]), "=f"(d0[37]), "=f"(d0[38]), "=f"(d0[39]),
      "=f"(d0[40]), "=f"(d0[41]), "=f"(d0[42]), "=f"(d0[43]), "=f"(d0[44]), "=f"(d0[45]), "=f"(d0[46]), "=f"(d0[47]),
      "=f"(d0[48]), "=f"(d0[49]), "=f"(d0[50]), "=f"(d0[51]), "=f"(d0[52]), "=f"(d0[53]), "=f"(d0[54]), "=f"(d0[55]),
      "=f"(d0[56]), "=f"(d0[57]), "=f"(d0[58]), "=f"(d0[59]), "=f"(d0[60]), "=f"(d0[61]), "=f"(d0[62]), "=f"(d0[63]),
      "=f"(d0[64]), "=f"(d0[65]), "=f"(d0[66]), "=f"(d0[67]), "=f"(d0[68]), "=f"(d0[69]), "=f"(d0[70]), "=f"(d0[71]),
      "=f"(d0[72]), "=f"(d0[73]), "=f"(d0[74]), "=f"(d0[75]), "=f"(d0[76]), "=f"(d0[77]), "=f"(d0[78]), "=f"(d0[79]),
      "=f"(d0[80]), "=f"(d0[81]), "=f"(d0[82]), "=f"(d0[83]), "=f"(d0[84]), "=f"(d0[85]), "=f"(d0[86]), "=f"(d0[87]),
      "=f"(d0[88]), "=f"(d0[89]), "=f"(d0[90]), "=f"(d0[91]), "=f"(d0[92]), "=f"(d0[93]), "=f"(d0[94]), "=f"(d0[95])
    : "l"(da), "l"(db));
}
enum { A_LOC = 0, A_X = 1, A_O = 2, A_H = 3 };
enum { W_QKV = 0, W_O = 1, W_G = 2, W_D = 3 };
enum { K_L = 0, K_E7 = 1, K_O7 = 2, K_OL = 3, K_OR = 4, K_LIN = 5 };
struct Seg { int nb, n, a, w, c0, c1, ks, dep; };
constexpr int NOA = 2;
constexpr Seg SEGS[NSEG] = {
  {3, 2, A_LOC, W_QKV, 1, 0, K_L, F_NONE},
  {3, 2, A_LOC, W_QKV, 0, 0, K_L, F_NONE},
  {3, 7, A_X, W_QKV, 0, 0, K_E7, F_X0},
  {3, 7, A_X, W_QKV, 0, 0, K_O7, F_X0B},
  {3, 7, A_X, W_QKV, 1, 0, K_E7, F_NONE},
  {3, 7, A_X, W_QKV, 1, 0, K_O7, F_NONE},
  {2, 8, A_O, W_O, 0, 0, K_LIN, F_O0},
  {2, 1, A_LOC, W_O, 0, 0, K_OL, F_NONE},
  {2, 7, A_O, W_O, 0, 0, K_OR, F_O1},
  {2, 2, A_LOC, W_G, 2, 0, K_L, F_NONE},
  {4, 2, A_LOC, W_G, 0, 1, K_L, F_NONE},
  {4, 7, A_X, W_G, 0, 1, K_E7, F_X1},
  {2, 7, A_X, W_G, 0, 0, K_O7, F_X1B},
  {4, 7, A_X, W_G, 2, 1, K_O7, F_NONE},
  {4, 7, A_X, W_G, 2, 3, K_E7, F_NONE},
  {4, 2, A_LOC, W_G, 4, 3, K_L, F_NONE},
  {4, 7, A_X, W_G, 4, 3, K_O7, F_NONE},
  {4, 7, A_X, W_G, 4, 5, K_E7, F_NONE},
  {4, 2, A_LOC, W_G, 6, 5, K_L, F_NONE},
  {4, 7, A_X, W_G, 6, 5, K_O7, F_NONE},
  {2, 7, A_X, W_G, 6, 0, K_E7, F_NONE},
  {2, 32, A_H, W_D, 0, 0, K_LIN, F_H0},
  {2, 24, A_H, W_D, 4, 0, K_LIN, F_H1},
};
constexpr Tabs make_tabs() {
  Tabs t{};
  int pa[2 * NST] = {}, pb[2 * NST] = {}, sa[2 * NST] = {}, sb[2 * NST] = {};
  int pos = 12, it = 0;
  constexpr int o0 = 32;
  for (int sg = 0; sg < 2 * NSEG; sg++) {
    Seg g = SEGS[sg % NSEG];
    if (sg < 6) { g.a = A_X; g.dep = F_NONE; }
    for (int k = 0; k < g.n; k++, it++) {
      const int cap = it % NST < o0 + 3 ? 20 : 24;
      const int a = (g.a == A_LOC && g.n > 1 && g.c0 < 4) ? 0 : 2, b = g.nb, rem = cap - pos;
      sa[it] = g.a == A_LOC ? 0 : 2; sb[it] = b;
      if (rem >= a + b) { pa[it] = pos; pb[it] = pos + a; pos += a + b; }
      else if (a && rem == a) { pa[it] = pos; pb[it] = 0; pos = b; }
      else if (a && rem == b) { pb[it] = pos; pa[it] = 0; pos = a; }
      else { pa[it] = 0; pb[it] = a; pos = a + b; }
      if (g.a == A_LOC) pa[it] = 24 + 2 * k;
    }
    t.seg[sg] = (uint32_t)(g.n | g.nb << 6 | g.a << 9 | g.w << 11 | g.c0 << 13 | g.c1 << 16 | g.ks << 19 | g.dep << 22);
  }
  for (int i = 0; i < 2 * NST; i++) {
    int lag[2] = {8, 8};
    const int p[2] = {pa[i], pb[i]}, n[2] = {sa[i], sb[i]}, io = i % NST - o0;
    for (int x = 0; x < 2; x++) {
      for (int l = i < 8 ? i : 8; l >= 1; l--) {
        const int q[2] = {pa[i - l], pb[i - l]}, m[2] = {sa[i - l], sb[i - l]};
        for (int y = 0; y < 2; y++)
          if (n[x] && m[y] && p[x] < q[y] + m[y] && q[y] < p[x] + n[x]) lag[x] = l;
      }
      if (io > 0 && io < 8 && p[x] >= 20 && io - NOA < lag[x]) lag[x] = io - NOA;
    }
    if (i == NST + 3) lag[1] = 6;
    if (i < o0 && lag[0] < lag[1]) lag[1] = lag[0];
    t.ring[i] = (uint32_t)(pa[i] * 512 | lag[1] | lag[0] << 4 | pb[i] * 512 << 16);
  }
  int waits[2 * NST] = {};
  for (int i = 0; i < 2 * NST; i++)
    for (int x = 0; x < 2; x++) {
      const int j = i - (int)((t.ring[i] >> (4 * x)) & 15);
      if (j >= 0 && (!x || (i >= o0 && sa[i]))) waits[j]++;
    }
  for (int j = 0; j < 2 * NST - 8; j++)
    for (int x = 1; x >= 0; x--)
      for (int i = j + 7; i > j && !waits[j]; i--) {
        const int q = i - (int)((t.ring[i] >> (4 * x)) & 15);
        if (q < j && waits[q] > 1 && (!x || sa[i])) { waits[q]--; waits[j]++; t.ring[i] -= (uint32_t)(j - q) << (4 * x); }
      }
  for (int jc = 0; jc < 8; jc++)
    for (int ks = 0; ks < K_LIN; ks++)
      for (int i = 0; i < 8; i++) {
        const int u = i == jc ? 7 : i;
        t.seq[jc][ks] |= (uint32_t)(ks == K_L ? jc * 2 + (i & 1) : ks == K_OL ? 8 + jc : ks == K_OR ? 8 + u : u * 2 + (ks != K_E7)) << (4 * i);
      }
  t.seq[8][K_L] = 0x10; t.seq[8][K_E7] = 0x8765432; t.seq[8][K_O7] = 0xfedcba9;
  return t;
}

constexpr uint32_t RING0 = make_tabs().ring[0];

__device__ __forceinline__ bool elect_one() {
  uint32_t pred;
  asm volatile("{\n.reg .pred p;\nelect.sync _|p, 0xffffffff;\nselp.u32 %0, 1, 0, p;\n}" : "=r"(pred));
  return pred;
}

struct Ctx {
  const Params& p;
  uint32_t sb;
  uint32_t it;
  uint32_t lp;
  uint32_t ebar;
  bool rel;
  uint32_t da, db;
  int w, wg, wi, lane;
  int rb, jc;
  float m0, r0, m1, r1;
};
struct Stage { uint64_t da, db; };
struct Stats { float2 a, b, c, d; };

__device__ __forceinline__ uint32_t ld_tag_s(uint32_t sb) { return __float_as_uint(lds32f(sb + MISC_OFF + M_TAG)); }
__device__ __forceinline__ void carrive(const Ctx& c, uint32_t bar) {
  __syncwarp();
  if (c.lane == 0) mbar_arrive(c.sb + MISC_OFF + bar);
}

__device__ __forceinline__ Stage peek(const Ctx& c) {
  const uint32_t e = c.p.t.ring[c.it];
  Stage s;
  asm("mov.b64 %0, {%1, 0x40000040};" : "=l"(s.da) : "r"(c.da + (e & 0x3e00)));
  asm("mov.b64 %0, {%1, 0x40000040};" : "=l"(s.db) : "r"(c.db + (e >> 16)));
  return s;
}
__device__ __forceinline__ void wait_full(Ctx& c) {
  mbar_wait(c.sb + MISC_OFF + B_FULL + (c.it & 7) * 8, (c.it >> 3) & 1);
  c.it++;
}
__device__ __forceinline__ void release(Ctx& c) {
  if (c.rel) asm volatile("mbarrier.arrive.shared::cluster.b64 _, [%0];" ::"r"(c.ebar) : "memory");
  c.ebar = (c.ebar + 8) & ~64u;
}
__device__ __forceinline__ void load_stats(const Ctx& c, Stats& s) {
  const int lane = pin(c.lane);
  const float2* sp = c.p.s->stats + (lane & 3) * 2 * SEQ + pin(c.rb) * 128 + pin(c.w) * 16 + (lane >> 2);
  s.a = ld_b64(sp); s.b = ld_b64(sp + SEQ); s.c = ld_b64(sp + 8); s.d = ld_b64(sp + SEQ + 8);
}
__device__ __forceinline__ void combine2(float2 a, float2 b, float& mean, float& rstd) {
  mean = qsum(a.x + b.x) * 0.125f;
  const float d0 = a.x - mean, d1 = b.x - mean;
  const float m2 = qsum(a.y + b.y + 128.f * (d0 * d0 + d1 * d1));
  rstd = rsqrtf(m2 * (1.f / 1024.f) + 1e-5f);
}
__device__ __forceinline__ void combine_stats(Ctx& c, Stats& s, uint32_t tag) {
  uint32_t n = 0;
  while (true) {
    const uint32_t x = tag & 1, y = tag >> 1;
    const uint32_t bad = (__float_as_uint(s.a.x) ^ x) | (__float_as_uint(s.b.x) ^ x) | (__float_as_uint(s.c.x) ^ x) | (__float_as_uint(s.d.x) ^ x) |
                         (__float_as_uint(s.a.y) ^ y) | (__float_as_uint(s.b.y) ^ y) | (__float_as_uint(s.c.y) ^ y) | (__float_as_uint(s.d.y) ^ y);
    if (__all_sync(0xffffffffu, !(bad & 1))) break;
    if (++n > (1u << 18)) __trap();
    load_stats(c, s);
  }
  combine2(s.a, s.b, c.m0, c.r0);
  combine2(s.c, s.d, c.m1, c.r1);
}

template <bool INIT> __device__ __forceinline__ void mm(float (&A)[64], uint64_t da, uint64_t db) {
  if (INIT) wgmma_n128_init(A, da, db); else wgmma_n128(A, da, db);
}
template <bool INIT> __device__ __forceinline__ void mm(float (&A)[96], uint64_t da, uint64_t db) {
  if (INIT) wgmma_n192_init(A, da, db); else wgmma_n192(A, da, db);
}
__device__ __forceinline__ void keep(float& v) { asm volatile("" : "+f"(v)); }
__device__ __forceinline__ void keep(uint32_t& v) { asm volatile("" : "+r"(v)); }
template <int N> __device__ __forceinline__ void keep_all(float (&A)[N]) {
#pragma unroll
  for (int i = 0; i < N; i++) keep(A[i]);
}
__device__ __forceinline__ void cut(const Stage& s) {
  asm volatile("{\n.reg .pred p;\nsetp.eq.u32 p, %0, 0xffffffff;\n@p trap;\n}" ::"r"((uint32_t)s.db) : "memory");
}
struct Nop { __device__ __forceinline__ void operator()() const {} };
template <bool INIT, bool FIRST, int WAIT = 1, int N, class HOOK>
__device__ __forceinline__ void step1(Ctx& c, Stage& s, float (&A)[N], HOOK&& hook) {
  wait_full(c);
  wgmma_fence();
  mm<INIT>(A, s.da, s.db);
  if (!FIRST) {
    wgmma_commit();
    wgmma_wait<1>();
    release(c);
  }
  mm<false>(A, s.da + 2, s.db + 128);
  mm<false>(A, s.da + 4, s.db + 256);
  wgmma_commit();
  mm<false>(A, s.da + 6, s.db + 384);
  wgmma_commit();
  s = peek(c);
  if (sizeof(hook) > 1) cut(s);
  hook();
  if (WAIT == 2 || (WAIT == 1 && sizeof(hook) == 1)) wgmma_wait<1>();
}
template <bool INIT, int WAIT = 1, class HOOK>
__device__ __forceinline__ void step2(Ctx& c, Stage& s, float (&A)[64], float (&B)[64], HOOK&& hook) {
  wait_full(c);
  wgmma_fence();
  mm<INIT>(A, s.da, s.db);
  mm<INIT>(B, s.da, s.db + 1024);
  wgmma_commit();
  wgmma_wait<1>();
  release(c);
  mm<false>(A, s.da + 2, s.db + 128);
  mm<false>(B, s.da + 2, s.db + 1152);
  mm<false>(A, s.da + 4, s.db + 256);
  mm<false>(B, s.da + 4, s.db + 1280);
  wgmma_commit();
  mm<false>(A, s.da + 6, s.db + 384);
  mm<false>(B, s.da + 6, s.db + 1408);
  wgmma_commit();
  s = peek(c);
  if (sizeof(hook) > 1) cut(s);
  hook();
  if (WAIT == 2 || (WAIT == 1 && sizeof(hook) == 1)) wgmma_wait<1>();
}
template <bool INIT>
__device__ __forceinline__ void stage128(float (&A)[64], uint64_t da, uint64_t db) {
  mm<INIT>(A, da, db);
  mm<false>(A, da + 2, db + 128);
  mm<false>(A, da + 4, db + 256);
  mm<false>(A, da + 6, db + 384);
}

__device__ __forceinline__ uint32_t warp_rows(const Ctx& c) { return c.sb + STG_OFF + pin(c.w) * 2048; }
__device__ __forceinline__ uint32_t stg_base(uint32_t rows, int lane) {
  return rows + (lane & 15) * 128 + (((lane >> 4) ^ (lane & 7)) << 4);
}
__device__ __forceinline__ int seq_row(const Ctx& c, int r) {
  const int w = pin(c.w);
  return pin(c.rb) * 128 + (w & 3) * 32 + (w >> 2) + 2 * r;
}
template <int H>
__device__ __forceinline__ void resid_init(const Ctx& c, float (&A)[64]) {
  const uint32_t sta = stg_base(warp_rows(c), pin(c.lane)) + H * 16384;
#pragma unroll
  for (int b = 0; b < 8; b += 2) {
    uint32_t v0, v1, v2, v3;
    ldsm4(sta ^ (b << 4), v0, v1, v2, v3);
    float* a = A + H * 32 + 4 * b;
    a[0] = bf_lo(v0); a[1] = bf_hi(v0); a[2] = bf_lo(v1); a[3] = bf_hi(v1);
    a[4] = bf_lo(v2); a[5] = bf_hi(v2); a[6] = bf_lo(v3); a[7] = bf_hi(v3);
  }
#pragma unroll
  for (int i = 0; i < 32; i++) keep(A[H * 32 + i]);
}
__device__ __forceinline__ void stats_acc(const Ctx& c, int h, Stats& t) {
  const uint32_t sta = (stg_base(warp_rows(c), pin(c.lane)) ^ ((h & 1) << 6)) + (h >> 1) * 16384;
  uint32_t v[8];
#pragma unroll
  for (int b = 0; b < 2; b++) ldsm4(sta ^ (b << 5), v[4 * b], v[4 * b + 1], v[4 * b + 2], v[4 * b + 3]);
#pragma unroll
  for (int i = 0; i < 8; i += 2) {
    const float a = bf_lo(v[i]), b = bf_hi(v[i]), d = bf_lo(v[i + 1]), e = bf_hi(v[i + 1]);
    t.a.x += a + b; t.b.x = fmaf(a, a, fmaf(b, b, t.b.x));
    t.a.y += d + e; t.b.y = fmaf(d, d, fmaf(e, e, t.b.y));
  }
}
__device__ __forceinline__ void stats_store(const Ctx& c, const Stats& t, uint32_t tag) {
  const int lane = pin(c.lane), rh = lane & 1;
  float sum = (rh ? t.a.y : t.a.x) + __shfl_xor_sync(0xffffffffu, rh ? t.a.x : t.a.y, 1);
  float sq = (rh ? t.b.y : t.b.x) + __shfl_xor_sync(0xffffffffu, rh ? t.b.x : t.b.y, 1);
  sum += __shfl_xor_sync(0xffffffffu, sum, 2);
  sq += __shfl_xor_sync(0xffffffffu, sq, 2);
  const float mu = sum * (1.f / 128.f), m2 = fmaxf(fmaf(-mu, sum, sq), 0.f);
  if (!(lane & 2))
    st_b64(c.p.s->stats + pin(c.jc) * SEQ + pin(c.rb) * 128 + pin(c.w) * 16 + (lane >> 2) + rh * 8,
           (__float_as_uint(mu) & ~1u) | (tag & 1), (__float_as_uint(m2) & ~1u) | (tag >> 1));
}
__device__ __forceinline__ void store_box(const Ctx& c, __nv_bfloat16* g, int h) {
  const int lane = pin(c.lane), r = lane >> 3, ch = lane & 7;
  const uint32_t rows = warp_rows(c) + r * 128 + h * 16384;
  g += (size_t)seq_row(c, r) * DM + pin(c.jc) * 128 + h * 64 + ch * 8;
  uint4 v[4];
#pragma unroll
  for (int i = 0; i < 4; i++) v[i] = lds128(rows + i * 512 + ((ch ^ ((r + 4 * i) & 7)) << 4));
#pragma unroll
  for (int i = 0; i < 4; i++) stg128(g + i * 8 * DM, v[i].x, v[i].y, v[i].z, v[i].w);
}
template <int H>
__device__ __forceinline__ void stage_box(uint32_t sta, const float (&A)[64]) {
#pragma unroll
  for (int b = 8 * H; b < 8 * H + 8; b += 2)
    stsm4((sta ^ ((b & 7) << 4)) + H * 16384, pack_bf16(A[4 * b], A[4 * b + 1]), pack_bf16(A[4 * b + 2], A[4 * b + 3]),
          pack_bf16(A[4 * b + 4], A[4 * b + 5]), pack_bf16(A[4 * b + 6], A[4 * b + 7]));
}
__device__ __forceinline__ void finish_x(Ctx& c, float (&A)[64], __nv_bfloat16* g) {
  const uint32_t sta = stg_base(warp_rows(c), pin(c.lane));
  wgmma_wait<0>();
  release(c);
  if (c.it == 2 * NST) cluster_arrive();
  keep_all(A);
  stage_box<0>(sta, A);
  __syncwarp();
  store_box(c, g, 0);
  carrive(c, B_DONE + c.wg * 8);
  stage_box<1>(sta, A);
  fence_proxy_async_smem();
  carrive(c, B_BOX1);
  bar_sync(2 + c.wg, 128);
}

struct Att { uint32_t q[16], k[16], kp[8], p[2][4], vp[8], vf[16]; float s[2][3][4], v[4][2], o[8][4]; };
struct Cs { float4 v[4]; };
__device__ __forceinline__ uint32_t vswz(int r) { return ((r & 1) << 2) | ((r >> 1) & 3); }
__device__ __forceinline__ uint32_t kv_base(const Ctx& c) { return c.sb + KV_OFF + (pin(c.w) >> 2) * KV_WG; }
__device__ __forceinline__ uint4* halo_ptr(const Params& p, int lp, int s, int rb, int jc, int wg, int lane) {
  return p.s->halo + (size_t)((((lp * 2 + s) * 16 + rb) * 8 + jc) * 2 + wg) * (5 * 32) + lane;
}
__device__ __forceinline__ void load_cs(const Ctx& c, int i, Cs& cs) {
  const uint32_t a = c.sb + CSQ_OFF + i * 256 + (pin(c.lane) & 3) * 16;
#pragma unroll
  for (int j = 0; j < 4; j++) cs.v[j] = lds128f(a + j * 64);
}
template <int B, bool KEEP>
__device__ __forceinline__ void fix_box(const Ctx& c, float (&acc)[96], const Cs& cs) {
#pragma unroll
  for (int j = 0; j < 4; j++) {
    float* a = acc + 32 * B + 8 * j;
    a[0] -= c.m0 * cs.v[j].x; a[1] -= c.m0 * cs.v[j].y; a[2] -= c.m1 * cs.v[j].x; a[3] -= c.m1 * cs.v[j].y;
    a[4] -= c.m0 * cs.v[j].z; a[5] -= c.m0 * cs.v[j].w; a[6] -= c.m1 * cs.v[j].z; a[7] -= c.m1 * cs.v[j].w;
  }
#pragma unroll
  for (int i = 0; i < 32; i++) if (KEEP) keep(acc[32 * B + i]);
}
template <int B>
__device__ __forceinline__ void pack_box(const float (&acc)[96], uint32_t (&f)[16]) {
#pragma unroll
  for (int i = 0; i < 16; i++) { f[i] = pack_bf16(acc[32 * B + 2 * i], acc[32 * B + 2 * i + 1]); keep(f[i]); }
}
__device__ __forceinline__ void halo_send(const Ctx& c, int s, int part, uint32_t (&f)[16]) {
  uint4* hp = halo_ptr(c.p, c.lp, s, pin(c.rb), pin(c.jc), c.wg, pin(c.lane)) + part * 64;
  f[7] = f[7] ? f[7] : 0x8000u;
  f[15] = f[15] ? f[15] : 0x8000u;
  st_tag_if(c.wi == 3, hp, f[1], f[3], f[5], f[7]);
  st_tag_if(c.wi == 3, hp + 32, f[9], f[11], f[13], f[15]);
}
__device__ __forceinline__ void halo_clear(const Ctx& c, int s) {
  uint4* hp = halo_ptr(c.p, c.lp, s, pin(c.rb), pin(c.jc), c.wg, pin(c.lane));
#pragma unroll
  for (int i = 0; i < 4; i++) st_tag_if(c.wi == 3, hp + i * 32, 0u, 0u, 0u, 0u);
  if (!s) st_tag_if(c.wi == 3, hp + 128, __float_as_uint(c.r1), 1u, 1u, 1u);
}
__device__ __forceinline__ void put_k(const Ctx& c, const uint32_t (&k)[16]) {
  const uint32_t a = kv_base(c) + KV_K + 1024 + c.wi * 1024 + pin(c.lane) * 16;
  sts128(a, k[1], k[3], k[5], k[7]);
  sts128(a + 512, k[9], k[11], k[13], k[15]);
}
__device__ __forceinline__ void put_v(const Ctx& c, const uint32_t (&v)[16]) {
  const int lane = pin(c.lane), g = lane >> 2;
  const uint32_t a = kv_base(c) + (8 + c.wi * 16 + g) * 128 + (((lane & 3) ^ vswz(g)) << 4);
#pragma unroll
  for (int i = 0; i < 4; i++) {
    const int hh = i >> 1, rh = i & 1;
    sts128((a ^ (hh << 6)) + rh * 1024, v[8 * hh + rh], v[8 * hh + 2 + rh], v[8 * hh + 4 + rh], v[8 * hh + 6 + rh]);
  }
}
__device__ __forceinline__ void put_rstd(const Ctx& c) {
  const int lane = pin(c.lane);
  if (!(lane & 2)) sts32f(kv_base(c) + KV_R + (8 + c.wi * 16 + (lane & 1) * 8 + (lane >> 2)) * 4, (lane & 1) ? c.r1 : c.r0);
}
__device__ __forceinline__ void get_rstd(const Ctx& c, float (&rk)[4]) {
  const int lane = pin(c.lane), g = lane >> 2, j = 2 * (lane & 3);
  const uint32_t a = kv_base(c) + KV_R + (c.wi * 16 + j) * 4, a0 = a + (j <= g ? 32 : 0), a1 = a + (j + 1 <= g ? 36 : 4);
  rk[0] = lds32f(a0); rk[1] = lds32f(a1); rk[2] = lds32f(a0 + 32); rk[3] = lds32f(a1 + 32);
}
__device__ __forceinline__ void halo_wait(const Ctx& c, int s) {
  if (c.wi == 0) mbar_wait(c.sb + MISC_OFF + B_HALO + c.wg * 8, s);
}
__device__ __forceinline__ void att_ldk(const Ctx& c, Att& t) {
  const uint32_t a = kv_base(c) + KV_K + c.wi * 1024 + pin(c.lane) * 16;
  const uint4 u = lds128(a), v = lds128(a + 512);
  t.kp[0] = u.x; t.kp[1] = u.y; t.kp[2] = u.z; t.kp[3] = u.w; t.kp[4] = v.x; t.kp[5] = v.y; t.kp[6] = v.z; t.kp[7] = v.w;
}
template <int W>
__device__ __forceinline__ void att_ldv(const Ctx& c, Att& t) {
  const int lane = pin(c.lane);
  const uint32_t vb = kv_base(c) + c.wi * 2048, sw = vswz(lane & 7);
  if (W & 2) {
    const uint32_t ap = vb + (lane & 7) * 128 + (((lane >> 3) ^ sw) << 4);
    ldsm4t(ap, t.vp[0], t.vp[1], t.vp[2], t.vp[3]);
    ldsm4t(ap ^ 64, t.vp[4], t.vp[5], t.vp[6], t.vp[7]);
  }
  if (W & 1) {
    const uint32_t ao = vb + 1024 + (lane & 15) * 128 + (((lane >> 4) ^ sw) << 4);
#pragma unroll
    for (int b = 0; b < 8; b += 2) ldsm4t(ao ^ (b << 4), t.vf[2 * b], t.vf[2 * b + 1], t.vf[2 * b + 2], t.vf[2 * b + 3]);
  }
}
template <int W>
__device__ __forceinline__ void att_s(Att& t) {
#pragma unroll
  for (int ks = 0; ks < 2; ks++)
#pragma unroll
    for (int i = (W & 1) ? 0 : 4; i < ((W & 2) ? 6 : 4); i++) {
      const int hh = i & 1, kb = 2 - (i >> 1);
      const uint32_t* q = t.q + 8 * hh + 4 * ks;
      const uint32_t b0 = kb ? t.k[8 * hh + 4 * ks + kb - 1] : t.kp[4 * hh + 2 * ks], b1 = kb ? t.k[8 * hh + 4 * ks + kb + 1] : t.kp[4 * hh + 2 * ks + 1];
      if (ks) mma16816(t.s[hh][kb], q[0], q[1], q[2], q[3], b0, b1); else mma16816z(t.s[hh][kb], q[0], q[1], q[2], q[3], b0, b1);
    }
}
__device__ __forceinline__ void att_exp(const Ctx& c, Att& t, const float (&rk)[4]) {
  const int lane = pin(c.lane), g = lane >> 2, j = 2 * (lane & 3);
  const bool u0 = j <= g, u1 = j + 1 <= g, first = c.rb == 0 && c.wi == 0;
  const float sc = 0.17677669529663687f * 1.4426950408889634f;
  const float c0 = sc * c.r0, c1 = sc * c.r1;
  const float b0 = (first && !u0) ? -INFINITY : 0.f, b1 = (first && !u1) ? -INFINITY : 0.f;
  float m[4];
#pragma unroll
  for (int hh = 0; hh < 2; hh++) {
    t.v[2 * hh][0] = fmaf(u0 ? t.s[hh][1][0] : t.s[hh][0][0], c0 * rk[0], b0);
    t.v[2 * hh][1] = fmaf(u1 ? t.s[hh][1][1] : t.s[hh][0][1], c0 * rk[1], b1);
    t.v[2 * hh + 1][0] = (u0 ? t.s[hh][2][2] : t.s[hh][1][2]) * (c1 * rk[2]);
    t.v[2 * hh + 1][1] = (u1 ? t.s[hh][2][3] : t.s[hh][1][3]) * (c1 * rk[3]);
  }
#pragma unroll
  for (int i = 0; i < 4; i++) m[i] = fmaxf(t.v[i][0], t.v[i][1]);
#pragma unroll
  for (int o = 1; o <= 2; o <<= 1)
#pragma unroll
    for (int i = 0; i < 4; i++) m[i] = fmaxf(m[i], __shfl_xor_sync(0xffffffffu, m[i], o));
#pragma unroll
  for (int i = 0; i < 4; i++) {
    t.v[i][0] = ex2(t.v[i][0] - m[i]);
    t.v[i][1] = ex2(t.v[i][1] - m[i]);
    keep(t.v[i][0]);
    keep(t.v[i][1]);
  }
}
__device__ __forceinline__ void att_p(const Ctx& c, Att& t, const float (&rk)[4]) {
  const int lane = pin(c.lane), g = lane >> 2, j = 2 * (lane & 3);
  float m[4];
#pragma unroll
  for (int i = 0; i < 4; i++) m[i] = t.v[i][0] + t.v[i][1];
#pragma unroll
  for (int o = 1; o <= 2; o <<= 1)
#pragma unroll
    for (int i = 0; i < 4; i++) m[i] += __shfl_xor_sync(0xffffffffu, m[i], o);
  const uint32_t mu = (j <= g ? 0xffffu : 0u) | (j + 1 <= g ? 0xffff0000u : 0u);
#pragma unroll
  for (int i = 0; i < 4; i++) {
    const float inv = rcp(m[i]);
    const uint32_t pp = pack_bf16(t.v[i][0] * rk[2 * (i & 1)] * inv, t.v[i][1] * rk[2 * (i & 1) + 1] * inv);
    t.p[i >> 1][(i & 1) * 2] = pp & ~mu;
    t.p[i >> 1][(i & 1) * 2 + 1] = pp & mu;
    keep(t.p[i >> 1][(i & 1) * 2]);
    keep(t.p[i >> 1][(i & 1) * 2 + 1]);
  }
}
__device__ __forceinline__ void att_pv(Att& t) {
#pragma unroll
  for (int b = 0; b < 8; b++) mma1688z(t.o[b], t.p[b >> 2][0], t.vp[b]);
#pragma unroll
  for (int b = 0; b < 8; b++) mma16816(t.o[b], t.p[b >> 2][1], t.p[b >> 2][2], 0u, t.p[b >> 2][3], t.vf[2 * b], t.vf[2 * b + 1]);
}
template <bool LOCAL>
__device__ __forceinline__ void att_out(const Ctx& c, int s, const Att& t) {
  const int lane = pin(c.lane), g = lane >> 2, tq = lane & 3;
  __nv_bfloat16* dst = c.p.s->o + (size_t)seq_row(c, g) * DM + (s * 8 + pin(c.jc)) * 64 + tq * 8;
  const uint32_t la = warp_rows(c) + g * 128 + ((tq ^ g) << 4);
  uint32_t v[16];
#pragma unroll
  for (int i = 0; i < 4; i++) {
    const int hh = i & 1, rh = i >> 1;
#pragma unroll
    for (int b = 0; b < 4; b++) v[4 * i + b] = pack_bf16(t.o[4 * hh + b][2 * rh], t.o[4 * hh + b][2 * rh + 1]);
  }
#pragma unroll
  for (int i = 0; i < 4; i++) stg128(dst + (i >> 1) * 16 * DM + (i & 1) * 32, v[4 * i], v[4 * i + 1], v[4 * i + 2], v[4 * i + 3]);
  carrive(c, B_DONE + c.wg * 8);
  if (LOCAL) {
#pragma unroll
    for (int i = 0; i < 4; i++) sts128((la ^ ((i & 1) << 6)) + (i >> 1) * 1024, v[4 * i], v[4 * i + 1], v[4 * i + 2], v[4 * i + 3]);
  }
}
__device__ __forceinline__ void halo_go(const Ctx& c) {
  if (c.wi == 0 && c.lane == 0) mbar_arrive(c.sb + MISC_OFF + B_HGO + c.wg * 8);
}

__device__ __forceinline__ void phase_a(Ctx& c, Stage& s) {
  float O[64];
  const uint32_t misc = c.sb + MISC_OFF, stag = c.lp * 2 + 1;
  Att t;
  float rk[4];
  {
    float U[96], V[96];
    step1<true, true>(c, s, V, Nop());
    step1<false, false>(c, s, V, Nop());
    step1<true, false>(c, s, U, Nop());
    {
      Stats st;
      st.a = st.b = st.c = st.d = make_float2(0.f, 0.f);
#pragma unroll 1
      for (int k = 0; k < 11; k++)
        step1<false, false, 2>(c, s, U, [&]() {
          if (k == 2) mbar_wait(misc + B_XL, 0);
          if (k >= 3 && k < 7) stats_acc(c, k - 3, st);
          if (k == 6) stats_store(c, st, stag);
          if (k == 9) load_stats(c, st);
        });
      step1<false, false>(c, s, U, [&]() { combine_stats(c, st, stag); mbar_wait(misc + B_CSQ + 8, 0); });
    }
#pragma unroll 1
    for (int k = 0; k < 3; k++) {
      Cs cs;
      load_cs(c, 3 + k, cs);
      step1<false, false, 2>(c, s, U, [&]() {
        if (k & 2) { fix_box<2, true>(c, V, cs); mbar_wait(misc + B_CSQ, 0); }
        else if (k & 1) fix_box<1, true>(c, V, cs);
        else { halo_clear(c, 0); fix_box<0, true>(c, V, cs); }
      });
    }
    {
      Cs cs;
      load_cs(c, 1, cs);
      step1<false, false>(c, s, V, [&]() { keep_all(U); fix_box<1, false>(c, U, cs); pack_box<1>(U, t.k); halo_send(c, 0, 0, t.k); put_k(c, t.k); });
      step1<false, false>(c, s, V, [&]() { load_cs(c, 2, cs); fix_box<2, false>(c, U, cs); pack_box<2>(U, t.vf); halo_send(c, 0, 1, t.vf); put_v(c, t.vf); load_cs(c, 0, cs); halo_go(c); });
      step1<false, false>(c, s, V, [&]() { fix_box<0, false>(c, U, cs); pack_box<0>(U, t.q); put_rstd(c); });
    }
    step1<false, false>(c, s, V, [&]() { halo_clear(c, 1); });
    step1<false, false>(c, s, V, [&]() { bar_sync(2 + c.wg, 128); halo_wait(c, 0); att_ldk(c, t); get_rstd(c, rk); });
    att_s<3>(t);
    step1<false, false>(c, s, V, [&]() { att_exp(c, t, rk); });
    step1<false, false>(c, s, V, [&]() { att_ldv<3>(c, t); att_p(c, t, rk); });
    att_pv(t);
    step1<false, false>(c, s, V, [&]() { att_out<false>(c, 0, t); });
    step1<false, false>(c, s, V, [&]() { resid_init<0>(c, O); });
    step1<false, false>(c, s, V, [&]() { resid_init<1>(c, O); });
#pragma unroll 1
    for (int k = 0; k < 4; k++) step1<false, false>(c, s, V, Nop());
    wgmma_wait<0>();
    release(c);
    keep_all(V);
    pack_box<1>(V, t.k); halo_send(c, 1, 0, t.k); put_k(c, t.k);
    pack_box<2>(V, t.vf); halo_send(c, 1, 1, t.vf); put_v(c, t.vf);
    pack_box<0>(V, t.q);
  }
  step1<false, true, 2>(c, s, O, [&]() { halo_go(c); });
  step1<false, false>(c, s, O, Nop());
  wgmma_wait<0>();
  release(c);
  bar_sync(1, 256);
  cut(s);
  att_ldv<1>(c, t);
  att_s<1>(t);
  halo_wait(c, 1);
  att_ldk(c, t);
  att_ldv<2>(c, t);
  att_s<2>(t);
  att_exp(c, t, rk);
  att_p(c, t, rk);
  att_pv(t);
  att_out<true>(c, 1, t);
  bar_sync(1, 256);
  step1<false, true>(c, s, O, Nop());
#pragma unroll 1
  for (int k = NOA + 1; k < 16; k++)
    step1<false, false, 2>(c, s, O, [&]() {
      if (k == 6) { fence_proxy_async_smem(); bar_sync(2 + c.wg, 128); }
    });
  finish_x(c, O, c.p.s->x);
}

template <int H>
__device__ __forceinline__ void scale_to(const Ctx& c, float (&E)[64], float (&A)[64]) {
  const float h0 = 0.5f * c.r0, h1 = 0.5f * c.r1;
#pragma unroll
  for (int i = (H & 1) ? 0 : 32; i < ((H & 2) ? 64 : 32); i++) {
    keep(A[i]);
    E[i] = A[i] * (i < 32 ? ((i & 2) ? h1 : h0) : ((i & 2) ? c.r1 : c.r0));
    keep(E[i]);
  }
}
template <int B>
__device__ __forceinline__ void piece(const Ctx& c, float (&A)[64], const float4 cs) {
  float h[4];
#pragma unroll
  for (int e = 0; e < 4; e++) {
    const float n = (e & 2) ? c.m1 : c.m0;
    const float a = fmaf(n, (e & 1) ? cs.y : cs.x, A[4 * B + e]), u = fmaf(n, (e & 1) ? cs.w : cs.z, A[32 + 4 * B + e]);
    const float w = a * u;
    h[e] = fmaf(w, tanh_approx(a), w);
  }
  A[4 * B] = __uint_as_float(pack_bf16(h[0], h[1]));
  A[4 * B + 1] = __uint_as_float(pack_bf16(h[2], h[3]));
  if (B == 7) carrive(c, B_CSFREE);
}
template <int B>
__device__ __forceinline__ void piece2(const Ctx& c, float (&E)[64], const float4 c0, const float4 c1) {
  piece<B>(c, E, c0);
  piece<B + 1>(c, E, c1);
}
template <int Q>
__device__ __forceinline__ void store_h2(const Ctx& c, const float (&E)[64], int blk) {
  const int lane = pin(c.lane);
  __nv_bfloat16* dst = c.p.s->h + (size_t)seq_row(c, lane >> 2) * FF + (blk * 8 + pin(c.jc)) * 64 + Q * 32 + (lane & 3) * 8;
#pragma unroll
  for (int rh = 0; rh < 2; rh++)
    stg128(dst + rh * 16 * FF, __float_as_uint(E[16 * Q + rh]), __float_as_uint(E[16 * Q + 4 + rh]),
           __float_as_uint(E[16 * Q + 8 + rh]), __float_as_uint(E[16 * Q + 12 + rh]));
}
__device__ __forceinline__ void tail_piece(const Ctx& c, float (&A)[64], const float4 cs, int k, int blk) {
  if (k < 4) {
    if (k < 2) { if (k == 0) piece<0>(c, A, cs); else piece<1>(c, A, cs); }
    else { if (k == 2) piece<2>(c, A, cs); else { piece<3>(c, A, cs); store_h2<0>(c, A, blk); } }
  } else {
    if (k < 6) { if (k == 4) piece<4>(c, A, cs); else piece<5>(c, A, cs); }
    else { if (k == 6) piece<6>(c, A, cs); else { piece<7>(c, A, cs); store_h2<1>(c, A, blk); } }
  }
}
template <int LOFF>
__device__ __forceinline__ void drain(Ctx& c, Stage& s, float (&L)[64], float (&M)[64], float (&E)[64]) {
  wait_full(c);
  wgmma_fence();
  stage128<false>(M, s.da, s.db + (1024 - LOFF));
  wgmma_commit();
  wgmma_wait<1>();
  release(c);
  scale_to<3>(c, E, L);
  wgmma_fence();
  stage128<true>(L, s.da, s.db + LOFF);
  wgmma_commit();
  s = peek(c);
}
__device__ __forceinline__ void phase_b(Ctx& c, Stage& s) {
  float X[64], Y[64], E[64];
  const uint32_t stag = (c.lp * 2 + 2) & 3;
  step1<true, true>(c, s, X, Nop());
  step1<false, false>(c, s, X, Nop());
  {
    Stats st;
    st.a = st.b = st.c = st.d = make_float2(0.f, 0.f);
    step2<true>(c, s, E, Y, Nop());
#pragma unroll 1
    for (int k = 0; k < 8; k++)
      step2<false, 2>(c, s, E, Y, [&]() {
        if (k < 4) stats_acc(c, k, st);
        if (k == 3) stats_store(c, st, stag);
        if (k == 5) load_stats(c, st);
        if (k == 7) { combine_stats(c, st, stag); c.m0 *= -c.r0; c.m1 *= -c.r1; }
      });
  }
#pragma unroll 1
  for (int k = 0; k < 7; k++) step1<false, false>(c, s, E, Nop());
  step2<false, 0>(c, s, X, Y, [&]() { scale_to<3>(c, E, E); });
#pragma unroll 1
  for (int blk = 0;; blk++) {
    mbar_wait(c.sb + MISC_OFF + B_CS, (blk + c.lp) & 1);
    const int n = blk == 2 ? 8 : 6;
#pragma unroll 1
    for (int k = 0; k < n; k++) {
      const uint32_t ca = c.sb + CSG_OFF + (k & 3) * 128 + (pin(c.lane) & 3) * 16;
      const float4 c0 = lds128f(ca), c1 = lds128f(ca + 64);
      step2<false, 2>(c, s, X, Y, [&]() {
        if (k & 4) {
          if (!(k & 3)) store_h2<0>(c, E, blk);
          else if (k == 5) { store_h2<1>(c, E, blk); if (blk == 3) carrive(c, B_DONE + c.wg * 8); }
        } else if (k & 2) {
          if (k & 1) piece2<6>(c, E, c0, c1); else piece2<4>(c, E, c0, c1);
        } else {
          if (k & 1) piece2<2>(c, E, c0, c1); else piece2<0>(c, E, c0, c1);
        }
      });
    }
    if (blk == 4) break;
    if (blk & 1) drain<0>(c, s, X, Y, E); else drain<1024>(c, s, Y, X, E);
  }
  step2<false>(c, s, X, Y, [&]() { resid_init<0>(c, E); });
  step2<false>(c, s, X, Y, [&]() { resid_init<1>(c, E); mbar_wait(c.sb + MISC_OFF + B_CS, (5 + c.lp) & 1); });
  step1<false, false>(c, s, X, [&]() { scale_to<1>(c, Y, Y); });
  step1<false, false>(c, s, X, [&]() { scale_to<2>(c, Y, Y); });
#pragma unroll 1
  for (int blk = 5;; blk++) {
#pragma unroll 1
    for (int k = 0; k < 8; k++) {
      const float4 cs = lds128f(c.sb + CSG_OFF + k * 64 + (pin(c.lane) & 3) * 16);
      if (blk == 5 && k < 5) step1<false, false, 0>(c, s, X, Nop()); else step1<false, false, 0>(c, s, E, Nop());
      tail_piece(c, Y, cs, k, blk);
      wgmma_wait<1>();
    }
    if (blk == 6) break;
    step1<false, false>(c, s, E, [&]() { scale_to<1>(c, Y, X); });
    step1<false, false>(c, s, E, [&]() { scale_to<2>(c, Y, X); mbar_wait(c.sb + MISC_OFF + B_CS, c.lp & 1); });
  }
  carrive(c, B_DONE + c.wg * 8);
#pragma unroll 1
  for (int k = 0; k < 43; k++) step1<false, false>(c, s, E, Nop());
  finish_x(c, E, c.lp ? c.p.out : c.p.s->x);
}

__device__ __forceinline__ void acc8(float (&a)[8], const uint4& v) {
  a[0] += bf_lo(v.x); a[1] += bf_hi(v.x); a[2] += bf_lo(v.y); a[3] += bf_hi(v.y);
  a[4] += bf_lo(v.z); a[5] += bf_hi(v.z); a[6] += bf_lo(v.w); a[7] += bf_hi(v.w);
}
__device__ __forceinline__ void st_sums(uint4* dst, const float (&a)[8], uint32_t tag) {
  uint32_t u[8];
#pragma unroll
  for (int i = 0; i < 8; i++) u[i] = (__float_as_uint(a[i]) & ~1u) | ((tag >> (i & 3)) & 1u);
  st_tag(dst, u[0], u[1], u[2], u[3]);
  st_tag(dst + 1, u[4], u[5], u[6], u[7]);
}
__device__ __forceinline__ bool add_sum(float4& a, const uint4& v, uint32_t tag) {
  a.x += __uint_as_float(v.x & ~1u); a.y += __uint_as_float(v.y & ~1u);
  a.z += __uint_as_float(v.z & ~1u); a.w += __uint_as_float(v.w & ~1u);
  return ((v.x & 1) | (v.y & 1) << 1 | (v.z & 1) << 2 | (v.w & 1) << 3) == (tag & 15);
}

__device__ __forceinline__ void spare_sum(const Params& p, uint32_t sb, int d, int w, int lane) {
  const int chunk = (w & 1) * 4 + (lane & 3), rg = lane >> 2;
  const uint32_t base = sb + (w >> 1) * 8192 + rg * 128 + ((chunk ^ rg) << 4);
  uint32_t slot = 0, par = 0;
#pragma unroll 1
  for (int t = d; t < 28; t += 4) {
    float a[8] = {0, 0, 0, 0, 0, 0, 0, 0};
#pragma unroll 1
    for (int k = 0; k < 16; k++) {
      mbar_wait_idle(sb + MISC_OFF + B_SFULL + slot * 8, par);
      uint4 v[8];
#pragma unroll
      for (int r = 0; r < 8; r++) v[r] = lds128(base + slot * 32768 + r * 1024);
#pragma unroll
      for (int r = 0; r < 8; r++) acc8(a, v[r]);
      __syncwarp();
      if (lane == 0) mbar_arrive(sb + MISC_OFF + B_SEMPTY + slot * 8);
      if (++slot == 6) { slot = 0; par ^= 1; }
    }
#pragma unroll 1
    for (int o = 16; o >= 4; o >>= 1)
#pragma unroll
      for (int i = 0; i < 8; i++) a[i] += __shfl_xor_sync(0xffffffffu, a[i], o);
    if (lane < 4) st_sums(p.s->part + (3 * DM + ((w >> 1) & 1) * FF + t * 128 + (w >> 2) * 64 + (w & 1) * 32) / 4 + lane * 2, a, ld_tag_s(sb));
  }
}
__device__ __forceinline__ void spare_load(const Params& p, uint32_t sb, int d, int lane) {
  uint32_t slot = 0, par = 1;
  const uint32_t want = ld_epoch(p) * 2 + 1, t0 = clock();
  while ((uint32_t)clock() - t0 < 13000) __nanosleep(200);
#pragma unroll 1
  for (int t = d; t < 28; t += 4) {
    if ((t >> 2) == 2) {
#pragma unroll 1
      for (uint32_t i = 0, n = 0; i < 4;) {
        const uint32_t v = ld_flag(reinterpret_cast<const uint8_t*>(p.s->flags + (i * 4 + (lane >> 3)) * 8 + F_X1B - 1) + (lane & 7) * 2);
        if (__all_sync(0xffffffffu, ((v - want) & 255) < 2)) i++; else __nanosleep(300);
        if (++n > (1u << 20)) __trap();
      }
    }
#pragma unroll 1
    for (int k = 0; k < 16; k++) {
      const uint32_t bar = sb + MISC_OFF + B_SFULL + slot * 8;
      mbar_wait(sb + MISC_OFF + B_SEMPTY + slot * 8, par);
      if (elect_one()) {
        mbar_expect_tx(bar, 32768);
#pragma unroll
        for (int b = 0; b < 4; b++) tma_load(sb + slot * 32768 + b * 8192, (b & 1) ? &p.wu : &p.wg, bar, t * 128 + (b >> 1) * 64, k * 64);
      }
      if (++slot == 6) { slot = 0; par ^= 1; }
    }
  }
}
__device__ __forceinline__ uint32_t qkv_sums(const Params& p, uint32_t sb, int q, int rb, int jc, int lane) {
  const uint32_t bar = sb + MISC_OFF + B_SLAB + q * 8, buf = sb + KV_OFF + q * 8192;
  const uint32_t tag = ld_epoch(p) + 1;
  mbar_wait_idle(sb + MISC_OFF + B_FULL, 0);
  const uint32_t t0 = clock();
  if (q == 0) {
    const int gx = (jc >> 1) - 1;
    if (gx >= 0) mbar_wait_idle(sb + MISC_OFF + B_EMPTY + gx * 8, 0);
    if (elect_one()) {
      mbar_expect_tx(sb + MISC_OFF + B_XL, 32768);
      tma_load3(sb + STG_OFF, &p.x0, sb + MISC_OFF + B_XL, jc * 128, rb * 64);
      tma_load3(sb + STG_OFF + 16384, &p.x0, sb + MISC_OFF + B_XL, jc * 128 + 64, rb * 64);
    }
  }
  {
    const int col = q * DM + ((rb & 1) * 8 + jc) * 64;
    float a[8] = {0.f, 0.f, 0.f, 0.f, 0.f, 0.f, 0.f, 0.f};
#pragma unroll 1
    for (int h = 0; h < 2; h++) {
      while (h && (uint32_t)clock() - t0 < 4600) __nanosleep(100);
      if (elect_one()) {
        mbar_expect_tx(bar, 8192);
        tma_load(buf, &p.wqkv, bar, col, ((rb & 14) + h) * 64);
        tma_load(buf + 4096, &p.wqkv, bar, col, ((rb & 14) + h) * 64 + 32);
      }
      mbar_wait_idle(bar, h);
      const uint32_t base = buf + (lane >> 3) * 128 + (((lane & 7) ^ (lane >> 3)) << 4);
#pragma unroll 1
      for (int r = 0; r < 8; r += 2) {
        const uint4 v0 = lds128(base + r * 1024), v1 = lds128((base ^ 64) + r * 1024 + 512);
        const uint4 v2 = lds128(base + r * 1024 + 1024), v3 = lds128((base ^ 64) + r * 1024 + 1536);
        acc8(a, v0); acc8(a, v1); acc8(a, v2); acc8(a, v3);
      }
      fence_proxy_async_smem();
      __syncwarp();
    }
#pragma unroll 1
    for (int o = 8; o <= 16; o <<= 1)
#pragma unroll
      for (int j = 0; j < 8; j++) a[j] += __shfl_xor_sync(0xffffffffu, a[j], o);
    if (lane < 8) st_sums(p.s->part + ((rb >> 1) * NCS + col) / 4 + lane * 2, a, tag);
  }
#pragma unroll 1
  for (int s = 1; s >= 0; s--) {
    const uint4* src = p.s->part + ((lane >> 4) * 4 * NCS + q * DM + (s * 8 + jc) * 64) / 4 + (lane & 15);
    float4 a;
    uint32_t n = 0;
    while (true) {
      uint4 v[4];
#pragma unroll
      for (int r = 0; r < 4; r++) v[r] = ld_tag(src + r * (NCS / 4));
      a = make_float4(0.f, 0.f, 0.f, 0.f);
      bool ok = true;
#pragma unroll
      for (int r = 0; r < 4; r++) ok = add_sum(a, v[r], tag) && ok;
      if (__all_sync(0xffffffffu, ok)) break;
      if (++n > (1u << 18)) __trap();
    }
    a.x += __shfl_xor_sync(0xffffffffu, a.x, 16); a.y += __shfl_xor_sync(0xffffffffu, a.y, 16);
    a.z += __shfl_xor_sync(0xffffffffu, a.z, 16); a.w += __shfl_xor_sync(0xffffffffu, a.w, 16);
    const uint32_t dst = sb + CSQ_OFF + (s * 3 + q) * 256 + ((lane & 15) >> 2) * 64 + (lane & 1) * 32 + (lane & 2) * 4 + (lane >> 4) * 16;
    sts64f(dst, lane < 16 ? a.x : a.z, lane < 16 ? a.y : a.w);
    __syncwarp();
    if (lane == 0) mbar_arrive(sb + MISC_OFF + B_CSQ + s * 8);
  }
  return tag;
}

struct Prod {
  const Params& p;
  uint32_t sb, it;
  uint32_t seq, kb, kinc;
};
__device__ __forceinline__ uint32_t seg_begin(Prod& pr, int sg, int jc) {
  const uint32_t d = pr.p.t.seg[sg], ks = (d >> 19) & 7;
  pr.seq = pr.p.t.seq[sg < 6 ? 8 : jc][ks];
  pr.kinc = ks == K_LIN;
  pr.kb = ks == K_LIN ? ((d >> 13) & 7) * 8 : 0;
  return d;
}
__device__ __forceinline__ int next_k(Prod& pr) {
  const int k = (pr.kb + (pr.seq & 15)) * 64;
  pr.seq >>= 4;
  pr.kb += pr.kinc;
  return k;
}
__device__ __forceinline__ void wait_released(const Prod& pr, uint32_t lag) {
  const uint32_t j = pr.it - lag;
  mbar_wait(pr.sb + MISC_OFF + B_EMPTY + (j & 7) * 8, (j >> 3) & 1);
}
template <int NB>
__device__ __forceinline__ void produce_b(Prod& pr, int n, uint32_t bytes, const CUtensorMap* tb, int c0, int c1, uint32_t rank,
                                          const CUtensorMap* ta, int arow) {
#pragma unroll 1
  for (; n > 0; n--) {
    const uint32_t e = pr.p.t.ring[pr.it];
    const int k = pin(next_k(pr));
    const uint32_t bar = pin(pr.sb + MISC_OFF + B_FULL + (pr.it & 7) * 8);
    const uint32_t b = pin(pr.sb + ((e >> 16) << 4) + rank * (NB == 3 ? 4096 : 8192));
    wait_released(pr, e & 15);
    if (elect_one()) {
      mbar_expect_tx(bar, bytes);
      if (NB == 3) {
#pragma unroll
        for (int q = 0; q < 3; q++) tma_load_mc(b + q * 8192, tb, bar, q * DM + c0, k + rank * 32);
        if (ta) tma_load3(pr.sb + ((e & 0x3e00) << 4), ta, bar, k, arow);
      } else if (NB == 5) {
        tma_load5_mc(b, tb, bar, c0, k >> 5);
      } else {
        tma_load_mc(b, tb, bar, c0, k);
        if (NB == 4) tma_load_mc(b + 16384, tb, bar, c1, k);
      }
    }
    pr.it++;
  }
}
__device__ __forceinline__ void cs_fill(const Params& p, uint32_t sb, int i, int jc, int lane, uint32_t tag) {
  const int blk = i >= 7 ? i - 7 : i, m = lane & 15;
  const uint4* src = p.s->part + (3 * DM + (lane >> 4) * FF + (blk * 8 + jc) * 64) / 4 + m;
  float4 a;
  uint32_t n = 0;
  while (true) {
    a = make_float4(0.f, 0.f, 0.f, 0.f);
    if (__all_sync(0xffffffffu, add_sum(a, ld_tag(src), tag))) break;
    if (++n > (1u << 18)) __trap();
    __nanosleep(500);
  }
  if (i > 0) mbar_wait_idle(sb + MISC_OFF + B_CSFREE, (i - 1) & 1);
  const float f = lane < 16 ? 0.5f : 1.f;
  const uint32_t dst = sb + CSG_OFF + m * 32 + (lane >> 4) * 8;
  sts64f(dst, a.x * f, a.y * f);
  sts64f(dst + 16, a.z * f, a.w * f);
  __syncwarp();
  if (lane == 0) mbar_arrive(sb + MISC_OFF + B_CS);
}

__global__ void __cluster_dims__(2, 1, 1) __launch_bounds__(384, 1)
fused_kernel(const __grid_constant__ Params p) {
  extern __shared__ __align__(1024) uint8_t smem_raw[];
  const uint32_t sb = smem_u32(smem_raw);
  const uint32_t misc = sb + MISC_OFF;
  const int warp = __shfl_sync(0xffffffffu, threadIdx.x >> 5, 0), lane = threadIdx.x & 31;
  uint32_t smid, nsmid;
  asm volatile("mov.u32 %0, %%smid;" : "=r"(smid));
  asm volatile("mov.u32 %0, %%nsmid;" : "=r"(nsmid));
  const int tpc = smid >> 1;
  const int cl = __shfl_sync(0xffffffffu, !(p.by_sm && nsmid == 132) ? (int)blockIdx.x >> 1 : tpc < 32 ? tpc
                           : tpc < 60 ? (4 + (tpc - 32) / 7) * 8 + 1 + (tpc - 32) % 7 : tpc < 62 ? tpc + 4 : (tpc - 58) * 8, 0);
  const uint32_t rank = blockIdx.x & 1;
  const int cta = cl * 2 + rank;
  const bool spare = cta >= NCTA;
  const int rb = (7 - (cl & 7)) * 2 + rank, jc = (cl >> 3) & 7;

  if (warp < 8) {
    if (warp < 2 && elect_one()) asm volatile("prefetch.tensormap [%0];" ::"l"(warp ? &p.x0 : &p.wqkv) : "memory");
    cluster_arrive();
    uint32_t tag = ld_epoch(p) + 1;
    cluster_wait();
    asm volatile("setmaxnreg.inc.sync.aligned.u32 232;");
    asm volatile("st.shared.u32 [%0], %1;" ::"r"(misc + M_TAG), "r"(tag) : "memory");
    if (spare) {
      spare_sum(p, sb, cta - NCTA, warp, lane);
      cluster_arrive();
    } else {
      Ctx c{p};
      c.sb = sb; c.w = warp; c.wg = warp >> 2; c.wi = warp & 3; c.lane = lane; c.rb = rb; c.jc = jc;
      c.rel = c.wi == 0 && lane < 2;
      asm("mapa.shared::cluster.u32 %0, %1, %2;" : "=r"(c.ebar) : "r"(misc + B_EMPTY), "r"(lane & 1));
      c.da = (((sb + c.wg * 8192) & 0x3FFFF) >> 4) | (1u << 16);
      c.db = ((sb & 0x3FFFF) >> 4) | ((8192u >> 4) << 16);
      c.it = 0;
      Stage s = peek(c);
#pragma unroll 1
      for (c.lp = 0; c.lp < 2; c.lp++) {
        phase_a(c, s);
        phase_b(c, s);
      }
      store_box(c, p.out, 1);
    }
  } else {
    asm volatile("setmaxnreg.dec.sync.aligned.u32 40;");
    if (elect_one()) {
      if (warp == 10) {
        for (int i = 0; i < 8; i++) mbar_init(misc + B_FULL + i * 8, 1);
      } else if (warp == 9) {
        if (sb & 1023) __trap();
        for (int i = 0; i < 8; i++) mbar_init(misc + B_EMPTY + i * 8, 4);
      } else if (warp == 8) {
        for (int i = 0; i < 2; i++) { mbar_init(misc + B_DONE + i * 8, 4); mbar_init(misc + B_HGO + i * 8, 1); mbar_init(misc + B_HALO + i * 8, 1); mbar_init(misc + B_CSQ + i * 8, 3); }
        mbar_init(misc + B_CS, 1); mbar_init(misc + B_XL, 1); mbar_init(misc + B_BOX1, 8); mbar_init(misc + B_CSFREE, 8);
      } else {
        for (int i = 0; i < 6; i++) { mbar_init(misc + B_SFULL + i * 8, 1); mbar_init(misc + B_SEMPTY + i * 8, 8); }
      }
      asm volatile("fence.mbarrier_init.release.cluster;" ::: "memory");
    }
    cluster_arrive();
    if (warp == 10 && !spare && elect_one()) {
      mbar_expect_tx(misc + B_FULL, 40960);
      tma_load3(sb + ((RING0 & 0x3e00) << 4), &p.x0, misc + B_FULL, 0, rb * 64);
#pragma unroll
      for (int i = 0; i < 6; i++) tma_load(sb + ((RING0 >> 16) << 4) + i * 4096, &p.wqkv, misc + B_FULL, (i >> 1) * DM + (8 + jc) * 64, (i & 1) * 32);
#pragma unroll 1
      for (int i = 1; i < 4; i++) tma_load3(sb + ((p.t.ring[i] & 0x3e00) << 4), &p.x0, misc + B_FULL + i * 8, (i & 1) * 64, rb * 64);
    }
    cluster_wait();
    if (spare) {
      if (warp == 8) {
        spare_load(p, sb, cta - NCTA, lane);
      }
    } else if (warp == 8) {
      Prod pr{p};
      pr.sb = sb; pr.it = 0;
#pragma unroll 1
      for (int sg = 0; sg < 2 * NSEG; sg++) {
        const uint32_t d = seg_begin(pr, sg, jc);
        if (sg == 0) { pr.seq >>= 4; pr.it = 1; }
        const int n = (d & 63) - (sg == 0), nb = (d >> 6) & 7, am = (d >> 9) & 3, wm = (d >> 11) & 3;
        const CUtensorMap* tb = &p.wqkv + (wm == W_D ? 4 : wm == W_G ? 2 + rank : wm);
        const int c0 = (wm & 1) ? jc * 128 + rank * 64 : (((d >> 13) & 7) * 8 + jc) * 64, c1 = (((d >> 16) & 7) * 8 + jc) * 64;
        const uint32_t bytes = nb * 8192 + (am ? 16384 : 0);
        if (nb == 3) produce_b<3>(pr, n, bytes, tb, c0, c1, rank, sg < 6 && sg > 1 ? &p.x0 : nullptr, rb * 64);
        else if (nb == 4) produce_b<4>(pr, n, bytes, tb, c0, c1, rank, nullptr, 0);
        else if (wm == W_D) produce_b<5>(pr, n, bytes, tb, c0, c1, rank, nullptr, 0);
        else produce_b<2>(pr, n, bytes, tb, c0, c1, rank, nullptr, 0);
      }
    } else {
      const uint32_t tag = qkv_sums(p, sb, warp - 9, rb, jc, lane);
      if (warp == 10) {
        Prod pr{p};
        pr.sb = sb; pr.it = 32;
        const uint8_t* fl = reinterpret_cast<const uint8_t*>(p.s->flags + rb * 8) + (lane & 15);
        mbar_wait_idle(misc + B_DONE, 0);
        uint32_t early = ~0u;
#pragma unroll 1
        for (int sg = 6; sg < 2 * NSEG; sg++) {
          const uint32_t d = seg_begin(pr, sg, jc), dep = d >> 22, am = (d >> 9) & 3;
          if (!am) { pr.it += d & 63; early = ~0u; continue; }
          const uint32_t want = (tag * 2 - (sg < NSEG)) & 255;
          uint32_t ready = dep ? __ballot_sync(0xffffffffu, early == want) : ~0u;
          if (dep) fence_proxy_async();
#pragma unroll 1
          for (int n = d & 63; n > 0; n--) {
            const uint32_t e = pr.p.t.ring[pr.it];
            const int k = pin(next_k(pr));
            const uint32_t bar = pin(misc + B_FULL + (pr.it & 7) * 8), a = pin(sb + ((e & 0x3e00) << 4));
            if (n == 1 && (pr.p.t.seg[sg + 1] >> 22)) early = ld_flag(fl + ((pr.p.t.seg[sg + 1] >> 22) - 1) * 16);
            if (am == A_X) wait_released(pr, (e >> 4) & 15);
            if (ready != ~0u) {
              const uint32_t need = (am == A_H || n == 1) ? ~0u : 3u << (am == A_X ? (k >> 6) & 14 : (k >> 5) & 14);
              if ((ready & need) != need) {
                const uint8_t* f = fl + (dep - 1) * 16;
                uint32_t v0 = ld_flag(f);
                const uint32_t t0 = clock();
                while ((uint32_t)clock() - t0 < 120) {}
                for (uint32_t i = 0;; i++) {
                  const uint32_t v1 = ld_flag(f);
                  ready = __ballot_sync(0xffffffffu, v0 == want);
                  if ((ready & need) == need) break;
                  v0 = ld_flag(f);
                  ready = __ballot_sync(0xffffffffu, v1 == want);
                  if ((ready & need) == need) break;
                  if (i > (1u << 19)) __trap();
                }
                fence_proxy_async();
              }
            }
            if (am != A_X) wait_released(pr, (e >> 4) & 15);
            if (elect_one()) tma_load3(a, &p.x0 + am, bar, k, rb * 64);
            pr.it++;
          }
        }
      } else {
        const int w = (warp - 9) >> 1;
        int ncs = 0;
#pragma unroll 1
        for (int ev = 0; ev < 14; ev++) {
          const int layer = ev >> 3, e = ev & 7;
          if (e < 2) {
            uint4* hp = halo_ptr(p, layer, e, rb - 1, jc, w, pin(lane));
            mbar_wait_idle(misc + B_HGO + w * 8, e);
            uint4 v[5];
            uint32_t n = 0;
#pragma unroll
            for (int i = 0; i < 5; i++) v[i] = make_uint4(0, 0, 0, 0);
            while (rb > 0) {
#pragma unroll
              for (int i = 0; i < 4; i++) v[i] = ld_tag(hp + i * 32);
              if (!e) v[4] = ld_tag(hp + 128);
              if (__all_sync(0xffffffffu, v[0].w && v[1].w && v[2].w && v[3].w && (e || v[4].w))) break;
              if (++n > (1u << 18)) __trap();
            }
            const int l = pin(lane);
            const uint32_t kv = sb + KV_OFF + w * KV_WG, d0 = kv + (l >> 2) * 128 + (((l & 3) ^ vswz(l >> 2)) << 4);
            sts128(kv + KV_K + l * 16, v[0].x, v[0].y, v[0].z, v[0].w);
            sts128(kv + KV_K + 512 + l * 16, v[1].x, v[1].y, v[1].z, v[1].w);
            sts128(d0, v[2].x, v[2].y, v[2].z, v[2].w);
            sts128(d0 ^ 64, v[3].x, v[3].y, v[3].z, v[3].w);
            if (!e) sts32f(kv + KV_R + (l >> 2) * 4, __uint_as_float(v[4].x));
            __syncwarp();
            if (lane == 0) mbar_arrive(misc + B_HALO + w * 8);
          }
          if (w == 1) {
            const int c1 = ev == 2 ? 1 : e == 4 ? 5 + 7 * layer : e == 5 ? 8 + 6 * layer : 0;
#pragma unroll 1
            for (; ncs < c1; ncs++) cs_fill(p, sb, ncs, jc, lane, tag);
          }
          uint8_t* flag = reinterpret_cast<uint8_t*>(p.s->flags + rb * 8 + e) + jc * 2 + w;
          if ((e & 3) == 3) {
            if (w == 0 && lane == 0) {
              mbar_wait(misc + B_BOX1, (ev >> 2) & 1);
              mbar_wait(misc + B_FULL + 4 * 8, ev > 3);
              tma_store3(&p.x, sb + STG_OFF + 16384, jc * 128 + 64, rb * 64);
              fence_gpu();
              st_flag(flag, tag * 2 - (ev < 6));
              st_flag(flag + 1, tag * 2 - (ev < 6));
            }
            continue;
          }
          mbar_wait_idle(misc + B_DONE + w * 8, (ev - (ev >> 2)) & 1);
          if (lane == 0) {
            fence_gpu();
            st_flag(flag, tag * 2 - (ev < 6));
          }
          if (e < 2 && rb > 0) {
            __syncwarp();
            uint4* hp = halo_ptr(p, layer, e, rb - 1, jc, w, pin(lane));
#pragma unroll 1
            for (int i = 0; i < 5; i++) st_tag(hp + i * 32, 0u, 0u, 0u, 0u);
          }
        }
      }
    }
    __syncwarp();
    if (threadIdx.x == 256) p.s->epoch[blockIdx.x] = ld_tag_s(sb);
    cluster_arrive();
  }
  cluster_wait();
}

typedef CUresult (*EncodeFn)(CUtensorMap*, CUtensorMapDataType, cuuint32_t, void*, const cuuint64_t*, const cuuint64_t*,
                             const cuuint32_t*, const cuuint32_t*, CUtensorMapInterleave, CUtensorMapSwizzle,
                             CUtensorMapL2promotion, CUtensorMapFloatOOBfill);

void make_map(EncodeFn fn, CUtensorMap* m, const void* ptr, uint64_t rows, uint64_t cols, uint32_t box_rows) {
  cuuint64_t dims[2] = {cols, rows};
  cuuint64_t strides[1] = {cols * 2};
  cuuint32_t box[2] = {64, box_rows};
  cuuint32_t es[2] = {1, 1};
  fn(m, CU_TENSOR_MAP_DATA_TYPE_BFLOAT16, 2, const_cast<void*>(ptr), dims, strides, box, es, CU_TENSOR_MAP_INTERLEAVE_NONE,
     CU_TENSOR_MAP_SWIZZLE_128B, CU_TENSOR_MAP_L2_PROMOTION_L2_256B, CU_TENSOR_MAP_FLOAT_OOB_FILL_NONE);
}

void make_act_map(EncodeFn fn, CUtensorMap* m, const void* ptr, uint64_t cols) {
  cuuint64_t dims[3] = {cols, SEQ / 2, 2};
  cuuint64_t strides[2] = {cols * 4, cols * 2};
  cuuint32_t box[3] = {64, 64, 2};
  cuuint32_t es[3] = {1, 1, 1};
  fn(m, CU_TENSOR_MAP_DATA_TYPE_BFLOAT16, 3, const_cast<void*>(ptr), dims, strides, box, es, CU_TENSOR_MAP_INTERLEAVE_NONE,
     CU_TENSOR_MAP_SWIZZLE_128B, CU_TENSOR_MAP_L2_PROMOTION_L2_128B, CU_TENSOR_MAP_FLOAT_OOB_FILL_NONE);
}

}

extern "C" void kernel_launch(void* const* d_in, const int* in_sizes, int n_in, void* d_out, int out_size) {
  (void)in_sizes; (void)n_in; (void)out_size;
  EncodeFn fn = nullptr;
  cudaDriverEntryPointQueryResult qr;
  cudaGetDriverEntryPoint("cuTensorMapEncodeTiled", (void**)&fn, cudaEnableDefault, &qr);
  Params p;
  cudaGetSymbolAddress((void**)&p.s, g_s);
  p.t = make_tabs();
  make_act_map(fn, &p.x0, d_in[0], DM);
  make_act_map(fn, &p.x, p.s->x, DM);
  make_act_map(fn, &p.o, p.s->o, DM);
  make_act_map(fn, &p.h, p.s->h, FF);
  make_map(fn, &p.wqkv, d_in[1], DM, 3 * DM, 32);
  make_map(fn, &p.wo, d_in[2], DM, DM, 64);
  make_map(fn, &p.wg, d_in[4], DM, FF, 64);
  make_map(fn, &p.wu, d_in[5], DM, FF, 64);
  {
    cuuint64_t dims[5] = {DM, 2, 4, 4, FF / 32};
    cuuint64_t strides[4] = {DM * 2, DM * 16, DM * 4, DM * 64};
    cuuint32_t box[5] = {64, 2, 4, 4, 2};
    cuuint32_t es[5] = {1, 1, 1, 1, 1};
    fn(&p.wd, CU_TENSOR_MAP_DATA_TYPE_BFLOAT16, 5, d_in[6], dims, strides, box, es, CU_TENSOR_MAP_INTERLEAVE_NONE,
       CU_TENSOR_MAP_SWIZZLE_128B, CU_TENSOR_MAP_L2_PROMOTION_L2_256B, CU_TENSOR_MAP_FLOAT_OOB_FILL_NONE);
  }
  p.out = (__nv_bfloat16*)d_out;
  cudaFuncSetAttribute(fused_kernel, cudaFuncAttributeMaxDynamicSharedMemorySize, SMEM_BYTES);
  {
    int dev = 0, sms = 0, nclusters = 0;
    cudaGetDevice(&dev);
    cudaDeviceGetAttribute(&sms, cudaDevAttrMultiProcessorCount, dev);
    cudaLaunchConfig_t cfg = {};
    cfg.gridDim = dim3(NCTA + NSPARE);
    cfg.blockDim = dim3(384);
    cfg.dynamicSmemBytes = SMEM_BYTES;
    cudaOccupancyMaxActiveClusters(&nclusters, fused_kernel, &cfg);
    p.by_sm = (sms == 132 && nclusters == 66) ? 1 : 0;
  }
  fused_kernel<<<NCTA + NSPARE, 384, SMEM_BYTES, cudaStreamPerThread>>>(p);
}
```

```cpp
#include <cuda_runtime.h>
#include <cuda_bf16.h>
#include <cuda.h>
#include <stdint.h>

namespace {

constexpr int SEQ = 2048, DM = 1024, FF = 3584;
constexpr int NCTA = 128;
constexpr uint32_t CAP = 196608;
constexpr uint32_t KV_OFF = 163840;
constexpr uint32_t KV_WG = 14848;
constexpr uint32_t KV_K = 9216, KV_R = 14336;
constexpr uint32_t STG_OFF = CAP;
constexpr uint32_t MISC_OFF = CAP + 32768;
constexpr uint32_t CSQ_OFF = MISC_OFF + 384;
constexpr uint32_t CSG_OFF = CSQ_OFF + 1536;
constexpr uint32_t SMEM_BYTES = CSG_OFF + 512 + 16;
constexpr int NSPARE = 4;

constexpr uint32_t B_EMPTY = 0, B_FULL = 64, B_DONE = 128  , B_HGO = 144  , B_HALO = 160  , B_CSQ = 176  ,
                   B_CS = 192, B_CSFREE = 200, B_XL = 216, B_BOX1 = 224, M_TAG = CSG_OFF + 512 - MISC_OFF,
                   B_SLAB = 256  , B_SFULL = 256, B_SEMPTY = 320;

enum { F_NONE = 0, F_O0, F_O1, F_X1, F_X1B, F_H0, F_H1, F_X0, F_X0B, F_COUNT };
constexpr int NCS = 3 * DM + 2 * FF;

struct Scratch {
  uint4 flags[16 * 8];
  uint32_t epoch[256];
  float2 stats[8 * SEQ];
  uint4 part[8 * NCS / 4];
  uint4 halo[4 * 16 * 8 * 2 * 5 * 32];
  __nv_bfloat16 x[SEQ * DM], o[SEQ * DM], h[SEQ * FF];
};
__device__ __align__(1024) Scratch g_s;

constexpr int NSEG = 23, NST = 168;
struct Tabs { uint32_t seg[2 * NSEG + 2], seq[9][8], ring[2 * NST + 2]; };
struct Params {
  Scratch* s;
  __nv_bfloat16* out;
  Tabs t;
  CUtensorMap x0, x, o, h, wqkv, wo, wg, wu, wd;
};

__device__ __forceinline__ uint32_t smem_u32(const void* p) { return (uint32_t)__cvta_generic_to_shared(p); }
__device__ __forceinline__ void mbar_init(uint32_t bar, uint32_t cnt) {
  asm volatile("mbarrier.init.shared::cta.b64 [%0], %1;" ::"r"(bar), "r"(cnt));
}
__device__ __forceinline__ void mbar_expect_tx(uint32_t bar, uint32_t bytes) {
  asm volatile("mbarrier.arrive.expect_tx.shared::cta.b64 _, [%0], %1;" ::"r"(bar), "r"(bytes) : "memory");
}
__device__ __forceinline__ void mbar_arrive(uint32_t bar) {
  asm volatile("mbarrier.arrive.shared::cta.b64 _, [%0];" ::"r"(bar) : "memory");
}
__device__ __forceinline__ bool mbar_try(uint32_t bar, uint32_t parity) {
  uint32_t ok;
  asm volatile("{\n.reg .pred p;\nmbarrier.try_wait.parity.shared::cta.b64 p, [%1], %2;\nselp.u32 %0, 1, 0, p;\n}"
               : "=r"(ok) : "r"(bar), "r"(parity) : "memory");
  return ok;
}
__device__ __forceinline__ void mbar_wait(uint32_t bar, uint32_t parity) {
  uint32_t n = 0;
  while (!mbar_try(bar, parity)) {
    if (++n > (1u << 20)) __trap();
  }
}
__device__ __forceinline__ void mbar_wait_idle(uint32_t bar, uint32_t parity) {
  uint32_t n = 0, ok;
  do {
    asm volatile("{\n.reg .pred p;\nmbarrier.try_wait.parity.shared::cta.b64 p, [%1], %2, %3;\nselp.u32 %0, 1, 0, p;\n}"
                 : "=r"(ok) : "r"(bar), "r"(parity), "n"(20000) : "memory");
    if (++n > (1u << 16)) __trap();
  } while (!ok);
}
__device__ __forceinline__ void tma_load(uint32_t dst, const void* tm, uint32_t bar, int c0, int c1) {
  asm volatile("cp.async.bulk.tensor.2d.shared::cluster.global.mbarrier::complete_tx::bytes [%0], [%1, {%3, %4}], [%2];"
               ::"r"(dst), "l"(tm), "r"(bar), "r"(c0), "r"(c1) : "memory");
}
__device__ __forceinline__ void tma_load3(uint32_t dst, const void* tm, uint32_t bar, int c0, int c1) {
  asm volatile("cp.async.bulk.tensor.3d.shared::cluster.global.mbarrier::complete_tx::bytes [%0], [%1, {%3, %4, %5}], [%2];"
               ::"r"(dst), "l"(tm), "r"(bar), "r"(c0), "r"(c1), "r"(0) : "memory");
}
__device__ __forceinline__ void tma_store3(const void* tm, uint32_t src, int c0, int c1) {
  asm volatile("cp.async.bulk.tensor.3d.global.shared::cta.bulk_group [%0, {%2, %3, %4}], [%1];\n"
               "cp.async.bulk.commit_group;\ncp.async.bulk.wait_group 0;" ::"l"(tm), "r"(src), "r"(c0), "r"(c1), "r"(0) : "memory");
}
__device__ __forceinline__ void tma_load_mc(uint32_t dst, const void* tm, uint32_t bar, int c0, int c1) {
  asm volatile("cp.async.bulk.tensor.2d.shared::cluster.global.mbarrier::complete_tx::bytes.multicast::cluster [%0], [%1, {%3, %4}], [%2], %5;"
               ::"r"(dst), "l"(tm), "r"(bar), "r"(c0), "r"(c1), "h"((uint16_t)3) : "memory");
}
__device__ __forceinline__ void tma_load5_mc(uint32_t dst, const void* tm, uint32_t bar, int c0, int c4) {
  asm volatile("cp.async.bulk.tensor.5d.shared::cluster.global.mbarrier::complete_tx::bytes.multicast::cluster [%0], [%1, {%3, %6, %6, %6, %4}], [%2], %5;"
               ::"r"(dst), "l"(tm), "r"(bar), "r"(c0), "r"(c4), "h"((uint16_t)3), "r"(0) : "memory");
}
__device__ __forceinline__ void fence_proxy_async() { asm volatile("fence.proxy.async.global;" ::: "memory"); }
__device__ __forceinline__ void st_tag(uint4* p, uint32_t a, uint32_t b, uint32_t c, uint32_t tag) {
  asm volatile("{\n.reg .b128 t;\n.reg .b64 lo, hi;\nmov.b64 lo, {%1, %2};\nmov.b64 hi, {%3, %4};\nmov.b128 t, {lo, hi};\n"
               "st.relaxed.gpu.global.b128 [%0], t;\n}" ::"l"(p), "r"(a), "r"(b), "r"(c), "r"(tag) : "memory");
}
__device__ __forceinline__ void st_tag_if(bool on, uint4* p, uint32_t a, uint32_t b, uint32_t c, uint32_t tag) {
  asm volatile("{\n.reg .b128 t;\n.reg .b64 lo, hi;\n.reg .pred p;\nsetp.ne.u32 p, %5, 0;\nmov.b64 lo, {%1, %2};\nmov.b64 hi, {%3, %4};\nmov.b128 t, {lo, hi};\n"
               "@p st.relaxed.gpu.global.b128 [%0], t;\n}" ::"l"(p), "r"(a), "r"(b), "r"(c), "r"(tag), "r"((uint32_t)on) : "memory");
}
__device__ __forceinline__ uint4 ld_tag(const uint4* p) {
  uint4 v;
  asm volatile("{\n.reg .b128 t;\n.reg .b64 lo, hi;\nld.relaxed.gpu.global.b128 t, [%4];\nmov.b128 {lo, hi}, t;\n"
               "mov.b64 {%0, %1}, lo;\nmov.b64 {%2, %3}, hi;\n}" : "=r"(v.x), "=r"(v.y), "=r"(v.z), "=r"(v.w) : "l"(p) : "memory");
  return v;
}
__device__ __forceinline__ float tanh_approx(float x) { float y; asm("tanh.approx.f32 %0, %1;" : "=f"(y) : "f"(x)); return y; }
__device__ __forceinline__ void fence_proxy_async_smem() { asm volatile("fence.proxy.async.shared::cta;" ::: "memory"); }
__device__ __forceinline__ void fence_gpu() { asm volatile("fence.release.gpu;" ::: "memory"); }
__device__ __forceinline__ uint32_t ld_epoch(const Params& p) {
  uint32_t e;
  asm volatile("ld.relaxed.gpu.global.u32 %0, [%1];" : "=r"(e) : "l"(p.s->epoch + blockIdx.x) : "memory");
  return e;
}
__device__ __forceinline__ void st_flag(void* p, uint32_t v) {
  asm volatile("st.relaxed.gpu.global.u8 [%0], %1;" ::"l"(p), "r"(v) : "memory");
}
__device__ __forceinline__ uint32_t ld_flag(const void* p) {
  uint32_t v;
  asm volatile("ld.relaxed.gpu.global.u8 %0, [%1];" : "=r"(v) : "l"(p) : "memory");
  return v;
}
__device__ __forceinline__ void wgmma_fence() { asm volatile("wgmma.fence.sync.aligned;" ::: "memory"); }
__device__ __forceinline__ void wgmma_commit() { asm volatile("wgmma.commit_group.sync.aligned;" ::: "memory"); }
template <int N> __device__ __forceinline__ void wgmma_wait() {
  asm volatile("wgmma.wait_group.sync.aligned %0;" ::"n"(N) : "memory");
}
__device__ __forceinline__ void cluster_arrive() { asm volatile("barrier.cluster.arrive.relaxed;" ::: "memory"); }
__device__ __forceinline__ void cluster_wait() { asm volatile("barrier.cluster.wait;" ::: "memory"); }
__device__ __forceinline__ void bar_sync(int id, int n) { asm volatile("bar.sync %0, %1;" ::"r"(id), "r"(n) : "memory"); }
__device__ __forceinline__ uint32_t pack_bf16(float lo, float hi) {
  uint32_t r;
  asm("cvt.rn.bf16x2.f32 %0, %1, %2;" : "=r"(r) : "f"(hi), "f"(lo));
  return r;
}
__device__ __forceinline__ float bf_lo(uint32_t v) { return __uint_as_float(v << 16); }
__device__ __forceinline__ float bf_hi(uint32_t v) { return __uint_as_float(v & 0xffff0000u); }
__device__ __forceinline__ void stsm4(uint32_t a, uint32_t r0, uint32_t r1, uint32_t r2, uint32_t r3) {
  asm volatile("stmatrix.sync.aligned.m8n8.x4.shared.b16 [%0], {%1, %2, %3, %4};" ::"r"(a), "r"(r0), "r"(r1), "r"(r2), "r"(r3) : "memory");
}
__device__ __forceinline__ void ldsm4(uint32_t a, uint32_t& r0, uint32_t& r1, uint32_t& r2, uint32_t& r3) {
  asm volatile("ldmatrix.sync.aligned.m8n8.x4.shared.b16 {%0, %1, %2, %3}, [%4];" : "=r"(r0), "=r"(r1), "=r"(r2), "=r"(r3) : "r"(a) : "memory");
}
__device__ __forceinline__ void ldsm4t(uint32_t a, uint32_t& r0, uint32_t& r1, uint32_t& r2, uint32_t& r3) {
  asm volatile("ldmatrix.sync.aligned.m8n8.x4.trans.shared.b16 {%0, %1, %2, %3}, [%4];" : "=r"(r0), "=r"(r1), "=r"(r2), "=r"(r3) : "r"(a) : "memory");
}
__device__ __forceinline__ void mma16816(float (&c)[4], uint32_t a0, uint32_t a1, uint32_t a2, uint32_t a3, uint32_t b0, uint32_t b1) {
  asm volatile("mma.sync.aligned.m16n8k16.row.col.f32.bf16.bf16.f32 {%0,%1,%2,%3}, {%4,%5,%6,%7}, {%8,%9}, {%0,%1,%2,%3};"
               : "+f"(c[0]), "+f"(c[1]), "+f"(c[2]), "+f"(c[3]) : "r"(a0), "r"(a1), "r"(a2), "r"(a3), "r"(b0), "r"(b1));
}
__device__ __forceinline__ float ex2(float x) { float y; asm("ex2.approx.ftz.f32 %0, %1;" : "=f"(y) : "f"(x)); return y; }
__device__ __forceinline__ float rcp(float x) { float y; asm("rcp.approx.ftz.f32 %0, %1;" : "=f"(y) : "f"(x)); return y; }
__device__ __forceinline__ uint32_t pin(uint32_t a) {
  uint32_t r;
  asm volatile("mov.u32 %0, %1;" : "=r"(r) : "r"(a) : "memory");
  return r;
}
__device__ __forceinline__ float lds32f(uint32_t a) {
  float v;
  asm volatile("ld.shared.f32 %0, [%1];" : "=f"(v) : "r"(a) : "memory");
  return v;
}
__device__ __forceinline__ void sts32f(uint32_t a, float v) { asm volatile("st.shared.f32 [%0], %1;" ::"r"(a), "f"(v) : "memory"); }
__device__ __forceinline__ void sts64f(uint32_t a, float x, float y) { asm volatile("st.shared.v2.f32 [%0], {%1, %2};" ::"r"(a), "f"(x), "f"(y) : "memory"); }
__device__ __forceinline__ float2 ld_b64(const void* p) {
  float2 v;
  asm volatile("{\n.reg .b64 t;\nld.relaxed.gpu.global.b64 t, [%2];\nmov.b64 {%0, %1}, t;\n}" : "=f"(v.x), "=f"(v.y) : "l"(p) : "memory");
  return v;
}
__device__ __forceinline__ void st_b64(void* p, uint32_t x, uint32_t y) {
  asm volatile("{\n.reg .b64 t;\nmov.b64 t, {%1, %2};\nst.relaxed.gpu.global.b64 [%0], t;\n}" ::"l"(p), "r"(x), "r"(y) : "memory");
}
__device__ __forceinline__ uint4 lds128(uint32_t a) {
  uint4 v;
  asm volatile("ld.shared.v4.u32 {%0, %1, %2, %3}, [%4];" : "=r"(v.x), "=r"(v.y), "=r"(v.z), "=r"(v.w) : "r"(a) : "memory");
  return v;
}
__device__ __forceinline__ float qsum(float v) {
  v += __shfl_xor_sync(0xffffffffu, v, 1);
  v += __shfl_xor_sync(0xffffffffu, v, 2);
  return v;
}
__device__ __forceinline__ void sts128(uint32_t a, uint32_t x, uint32_t y, uint32_t z, uint32_t w) {
  asm volatile("st.shared.v4.u32 [%0], {%1, %2, %3, %4};" ::"r"(a), "r"(x), "r"(y), "r"(z), "r"(w) : "memory");
}
__device__ __forceinline__ float4 lds128f(uint32_t a) {
  float4 v;
  asm volatile("ld.shared.v4.f32 {%0, %1, %2, %3}, [%4];" : "=f"(v.x), "=f"(v.y), "=f"(v.z), "=f"(v.w) : "r"(a) : "memory");
  return v;
}
__device__ __forceinline__ void stg128(void* p, uint32_t x, uint32_t y, uint32_t z, uint32_t w) {
  asm volatile("st.global.v4.u32 [%0], {%1, %2, %3, %4};" ::"l"(p), "r"(x), "r"(y), "r"(z), "r"(w) : "memory");
}
__device__ __forceinline__ void mma1688z(float (&c)[4], uint32_t a0, uint32_t b0) {
  asm volatile("mma.sync.aligned.m16n8k8.row.col.f32.bf16.bf16.f32 {%0,%1,%2,%3}, {%4,%5}, {%6}, {%7,%7,%7,%7};"
               : "=f"(c[0]), "=f"(c[1]), "=f"(c[2]), "=f"(c[3]) : "r"(a0), "r"(0u), "r"(b0), "f"(0.f));
}
__device__ __forceinline__ void mma16816z(float (&c)[4], uint32_t a0, uint32_t a1, uint32_t a2, uint32_t a3, uint32_t b0, uint32_t b1) {
  asm volatile("mma.sync.aligned.m16n8k16.row.col.f32.bf16.bf16.f32 {%0,%1,%2,%3}, {%4,%5,%6,%7}, {%8,%9}, {%10,%10,%10,%10};"
               : "=f"(c[0]), "=f"(c[1]), "=f"(c[2]), "=f"(c[3]) : "r"(a0), "r"(a1), "r"(a2), "r"(a3), "r"(b0), "r"(b1), "f"(0.f));
}

__device__ __forceinline__ void wgmma_n128(float (&d0)[64], uint64_t da, uint64_t db) {
  asm volatile(
    "wgmma.mma_async.sync.aligned.m64n128k16.f32.bf16.bf16 "
    "{%0,%1,%2,%3,%4,%5,%6,%7,%8,%9,%10,%11,%12,%13,%14,%15,"
    "%16,%17,%18,%19,%20,%21,%22,%23,%24,%25,%26,%27,%28,%29,%30,%31,"
    "%32,%33,%34,%35,%36,%37,%38,%39,%40,%41,%42,%43,%44,%45,%46,%47,"
    "%48,%49,%50,%51,%52,%53,%54,%55,%56,%57,%58,%59,%60,%61,%62,%63},"
    " %64, %65, 1, 1, 1, 0, 1;"
    : "+f"(d0[0]), "+f"(d0[1]), "+f"(d0[2]), "+f"(d0[3]), "+f"(d0[4]), "+f"(d0[5]), "+f"(d0[6]), "+f"(d0[7]),
      "+f"(d0[8]), "+f"(d0[9]), "+f"(d0[10]), "+f"(d0[11]), "+f"(d0[12]), "+f"(d0[13]), "+f"(d0[14]), "+f"(d0[15]),
      "+f"(d0[16]), "+f"(d0[17]), "+f"(d0[18]), "+f"(d0[19]), "+f"(d0[20]), "+f"(d0[21]), "+f"(d0[22]), "+f"(d0[23]),
      "+f"(d0[24]), "+f"(d0[25]), "+f"(d0[26]), "+f"(d0[27]), "+f"(d0[28]), "+f"(d0[29]), "+f"(d0[30]), "+f"(d0[31]),
      "+f"(d0[32]), "+f"(d0[33]), "+f"(d0[34]), "+f"(d0[35]), "+f"(d0[36]), "+f"(d0[37]), "+f"(d0[38]), "+f"(d0[39]),
      "+f"(d0[40]), "+f"(d0[41]), "+f"(d0[42]), "+f"(d0[43]), "+f"(d0[44]), "+f"(d0[45]), "+f"(d0[46]), "+f"(d0[47]),
      "+f"(d0[48]), "+f"(d0[49]), "+f"(d0[50]), "+f"(d0[51]), "+f"(d0[52]), "+f"(d0[53]), "+f"(d0[54]), "+f"(d0[55]),
      "+f"(d0[56]), "+f"(d0[57]), "+f"(d0[58]), "+f"(d0[59]), "+f"(d0[60]), "+f"(d0[61]), "+f"(d0[62]), "+f"(d0[63])
    : "l"(da), "l"(db));
}
__device__ __forceinline__ void wgmma_n128_init(float (&d0)[64], uint64_t da, uint64_t db) {
  asm volatile(
    "wgmma.mma_async.sync.aligned.m64n128k16.f32.bf16.bf16 "
    "{%0,%1,%2,%3,%4,%5,%6,%7,%8,%9,%10,%11,%12,%13,%14,%15,"
    "%16,%17,%18,%19,%20,%21,%22,%23,%24,%25,%26,%27,%28,%29,%30,%31,"
    "%32,%33,%34,%35,%36,%37,%38,%39,%40,%41,%42,%43,%44,%45,%46,%47,"
    "%48,%49,%50,%51,%52,%53,%54,%55,%56,%57,%58,%59,%60,%61,%62,%63},"
    " %64, %65, 0, 1, 1, 0, 1;"
    : "=f"(d0[0]), "=f"(d0[1]), "=f"(d0[2]), "=f"(d0[3]), "=f"(d0[4]), "=f"(d0[5]), "=f"(d0[6]), "=f"(d0[7]),
      "=f"(d0[8]), "=f"(d0[9]), "=f"(d0[10]), "=f"(d0[11]), "=f"(d0[12]), "=f"(d0[13]), "=f"(d0[14]), "=f"(d0[15]),
      "=f"(d0[16]), "=f"(d0[17]), "=f"(d0[18]), "=f"(d0[19]), "=f"(d0[20]), "=f"(d0[21]), "=f"(d0[22]), "=f"(d0[23]),
      "=f"(d0[24]), "=f"(d0[25]), "=f"(d0[26]), "=f"(d0[27]), "=f"(d0[28]), "=f"(d0[29]), "=f"(d0[30]), "=f"(d0[31]),
      "=f"(d0[32]), "=f"(d0[33]), "=f"(d0[34]), "=f"(d0[35]), "=f"(d0[36]), "=f"(d0[37]), "=f"(d0[38]), "=f"(d0[39]),
      "=f"(d0[40]), "=f"(d0[41]), "=f"(d0[42]), "=f"(d0[43]), "=f"(d0[44]), "=f"(d0[45]), "=f"(d0[46]), "=f"(d0[47]),
      "=f"(d0[48]), "=f"(d0[49]), "=f"(d0[50]), "=f"(d0[51]), "=f"(d0[52]), "=f"(d0[53]), "=f"(d0[54]), "=f"(d0[55]),
      "=f"(d0[56]), "=f"(d0[57]), "=f"(d0[58]), "=f"(d0[59]), "=f"(d0[60]), "=f"(d0[61]), "=f"(d0[62]), "=f"(d0[63])
    : "l"(da), "l"(db));
}
__device__ __forceinline__ void wgmma_n192(float (&d0)[96], uint64_t da, uint64_t db) {
  asm volatile(
    "wgmma.mma_async.sync.aligned.m64n192k16.f32.bf16.bf16 "
    "{%0,%1,%2,%3,%4,%5,%6,%7,%8,%9,%10,%11,%12,%13,%14,%15,"
    "%16,%17,%18,%19,%20,%21,%22,%23,%24,%25,%26,%27,%28,%29,%30,%31,"
    "%32,%33,%34,%35,%36,%37,%38,%39,%40,%41,%42,%43,%44,%45,%46,%47,"
    "%48,%49,%50,%51,%52,%53,%54,%55,%56,%57,%58,%59,%60,%61,%62,%63,"
    "%64,%65,%66,%67,%68,%69,%70,%71,%72,%73,%74,%75,%76,%77,%78,%79,"
    "%80,%81,%82,%83,%84,%85,%86,%87,%88,%89,%90,%91,%92,%93,%94,%95},"
    " %96, %97, 1, 1, 1, 0, 1;"
    : "+f"(d0[0]), "+f"(d0[1]), "+f"(d0[2]), "+f"(d0[3]), "+f"(d0[4]), "+f"(d0[5]), "+f"(d0[6]), "+f"(d0[7]),
      "+f"(d0[8]), "+f"(d0[9]), "+f"(d0[10]), "+f"(d0[11]), "+f"(d0[12]), "+f"(d0[13]), "+f"(d0[14]), "+f"(d0[15]),
      "+f"(d0[16]), "+f"(d0[17]), "+f"(d0[18]), "+f"(d0[19]), "+f"(d0[20]), "+f"(d0[21]), "+f"(d0[22]), "+f"(d0[23]),
      "+f"(d0[24]), "+f"(d0[25]), "+f"(d0[26]), "+f"(d0[27]), "+f"(d0[28]), "+f"(d0[29]), "+f"(d0[30]), "+f"(d0[31]),
      "+f"(d0[32]), "+f"(d0[33]), "+f"(d0[34]), "+f"(d0[35]), "+f"(d0[36]), "+f"(d0[37]), "+f"(d0[38]), "+f"(d0[39]),
      "+f"(d0[40]), "+f"(d0[41]), "+f"(d0[42]), "+f"(d0[43]), "+f"(d0[44]), "+f"(d0[45]), "+f"(d0[46]), "+f"(d0[47]),
      "+f"(d0[48]), "+f"(d0[49]), "+f"(d0[50]), "+f"(d0[51]), "+f"(d0[52]), "+f"(d0[53]), "+f"(d0[54]), "+f"(d0[55]),
      "+f"(d0[56]), "+f"(d0[57]), "+f"(d0[58]), "+f"(d0[59]), "+f"(d0[60]), "+f"(d0[61]), "+f"(d0[62]), "+f"(d0[63]),
      "+f"(d0[64]), "+f"(d0[65]), "+f"(d0[66]), "+f"(d0[67]), "+f"(d0[68]), "+f"(d0[69]), "+f"(d0[70]), "+f"(d0[71]),
      "+f"(d0[72]), "+f"(d0[73]), "+f"(d0[74]), "+f"(d0[75]), "+f"(d0[76]), "+f"(d0[77]), "+f"(d0[78]), "+f"(d0[79]),
      "+f"(d0[80]), "+f"(d0[81]), "+f"(d0[82]), "+f"(d0[83]), "+f"(d0[84]), "+f"(d0[85]), "+f"(d0[86]), "+f"(d0[87]),
      "+f"(d0[88]), "+f"(d0[89]), "+f"(d0[90]), "+f"(d0[91]), "+f"(d0[92]), "+f"(d0[93]), "+f"(d0[94]), "+f"(d0[95])
    : "l"(da), "l"(db));
}
__device__ __forceinline__ void wgmma_n192_init(float (&d0)[96], uint64_t da, uint64_t db) {
  asm volatile(
    "wgmma.mma_async.sync.aligned.m64n192k16.f32.bf16.bf16 "
    "{%0,%1,%2,%3,%4,%5,%6,%7,%8,%9,%10,%11,%12,%13,%14,%15,"
    "%16,%17,%18,%19,%20,%21,%22,%23,%24,%25,%26,%27,%28,%29,%30,%31,"
    "%32,%33,%34,%35,%36,%37,%38,%39,%40,%41,%42,%43,%44,%45,%46,%47,"
    "%48,%49,%50,%51,%52,%53,%54,%55,%56,%57,%58,%59,%60,%61,%62,%63,"
    "%64,%65,%66,%67,%68,%69,%70,%71,%72,%73,%74,%75,%76,%77,%78,%79,"
    "%80,%81,%82,%83,%84,%85,%86,%87,%88,%89,%90,%91,%92,%93,%94,%95},"
    " %96, %97, 0, 1, 1, 0, 1;"
    : "=f"(d0[0]), "=f"(d0[1]), "=f"(d0[2]), "=f"(d0[3]), "=f"(d0[4]), "=f"(d0[5]), "=f"(d0[6]), "=f"(d0[7]),
      "=f"(d0[8]), "=f"(d0[9]), "=f"(d0[10]), "=f"(d0[11]), "=f"(d0[12]), "=f"(d0[13]), "=f"(d0[14]), "=f"(d0[15]),
      "=f"(d0[16]), "=f"(d0[17]), "=f"(d0[18]), "=f"(d0[19]), "=f"(d0[20]), "=f"(d0[21]), "=f"(d0[22]), "=f"(d0[23]),
      "=f"(d0[24]), "=f"(d0[25]), "=f"(d0[26]), "=f"(d0[27]), "=f"(d0[28]), "=f"(d0[29]), "=f"(d0[30]), "=f"(d0[31]),
      "=f"(d0[32]), "=f"(d0[33]), "=f"(d0[34]), "=f"(d0[35]), "=f"(d0[36]), "=f"(d0[37]), "=f"(d0[38]), "=f"(d0[39]),
      "=f"(d0[40]), "=f"(d0[41]), "=f"(d0[42]), "=f"(d0[43]), "=f"(d0[44]), "=f"(d0[45]), "=f"(d0[46]), "=f"(d0[47]),
      "=f"(d0[48]), "=f"(d0[49]), "=f"(d0[50]), "=f"(d0[51]), "=f"(d0[52]), "=f"(d0[53]), "=f"(d0[54]), "=f"(d0[55]),
      "=f"(d0[56]), "=f"(d0[57]), "=f"(d0[58]), "=f"(d0[59]), "=f"(d0[60]), "=f"(d0[61]), "=f"(d0[62]), "=f"(d0[63]),
      "=f"(d0[64]), "=f"(d0[65]), "=f"(d0[66]), "=f"(d0[67]), "=f"(d0[68]), "=f"(d0[69]), "=f"(d0[70]), "=f"(d0[71]),
      "=f"(d0[72]), "=f"(d0[73]), "=f"(d0[74]), "=f"(d0[75]), "=f"(d0[76]), "=f"(d0[77]), "=f"(d0[78]), "=f"(d0[79]),
      "=f"(d0[80]), "=f"(d0[81]), "=f"(d0[82]), "=f"(d0[83]), "=f"(d0[84]), "=f"(d0[85]), "=f"(d0[86]), "=f"(d0[87]),
      "=f"(d0[88]), "=f"(d0[89]), "=f"(d0[90]), "=f"(d0[91]), "=f"(d0[92]), "=f"(d0[93]), "=f"(d0[94]), "=f"(d0[95])
    : "l"(da), "l"(db));
}
enum { A_LOC = 0, A_X = 1, A_O = 2, A_H = 3 };
enum { W_QKV = 0, W_O = 1, W_G = 2, W_D = 3 };
enum { K_L = 0, K_E7 = 1, K_O7 = 2, K_OL = 3, K_OR = 4, K_LIN = 5 };
struct Seg { int nb, n, a, w, c0, c1, ks, dep; };
constexpr int NOA = 2;
constexpr Seg SEGS[NSEG] = {
  {3, 2, A_LOC, W_QKV, 1, 0, K_L, F_NONE},
  {3, 2, A_LOC, W_QKV, 0, 0, K_L, F_NONE},
  {3, 7, A_X, W_QKV, 0, 0, K_E7, F_X0},
  {3, 7, A_X, W_QKV, 0, 0, K_O7, F_X0B},
  {3, 7, A_X, W_QKV, 1, 0, K_E7, F_NONE},
  {3, 7, A_X, W_QKV, 1, 0, K_O7, F_NONE},
  {2, 8, A_O, W_O, 0, 0, K_LIN, F_O0},
  {2, 1, A_LOC, W_O, 0, 0, K_OL, F_NONE},
  {2, 7, A_O, W_O, 0, 0, K_OR, F_O1},
  {2, 2, A_LOC, W_G, 2, 0, K_L, F_NONE},
  {4, 2, A_LOC, W_G, 0, 1, K_L, F_NONE},
  {4, 7, A_X, W_G, 0, 1, K_E7, F_X1},
  {2, 7, A_X, W_G, 0, 0, K_O7, F_X1B},
  {4, 7, A_X, W_G, 2, 1, K_O7, F_NONE},
  {4, 7, A_X, W_G, 2, 3, K_E7, F_NONE},
  {4, 2, A_LOC, W_G, 4, 3, K_L, F_NONE},
  {4, 7, A_X, W_G, 4, 3, K_O7, F_NONE},
  {4, 7, A_X, W_G, 4, 5, K_E7, F_NONE},
  {4, 2, A_LOC, W_G, 6, 5, K_L, F_NONE},
  {4, 7, A_X, W_G, 6, 5, K_O7, F_NONE},
  {2, 7, A_X, W_G, 6, 0, K_E7, F_NONE},
  {2, 32, A_H, W_D, 0, 0, K_LIN, F_H0},
  {2, 24, A_H, W_D, 4, 0, K_LIN, F_H1},
};
constexpr Tabs make_tabs() {
  Tabs t{};
  int pa[2 * NST] = {}, pb[2 * NST] = {}, sa[2 * NST] = {}, sb[2 * NST] = {};
  int pos = 12, it = 0;
  constexpr int o0 = 32;
  for (int sg = 0; sg < 2 * NSEG; sg++) {
    Seg g = SEGS[sg % NSEG];
    if (sg < 6) { g.a = A_X; g.dep = F_NONE; }
    for (int k = 0; k < g.n; k++, it++) {
      const int cap = it % NST < o0 + 3 ? 20 : 24;
      const int a = (g.a == A_LOC && g.n > 1 && g.c0 < 4) ? 0 : 2, b = g.nb, rem = cap - pos;
      sa[it] = g.a == A_LOC ? 0 : 2; sb[it] = b;
      if (rem >= a + b) { pa[it] = pos; pb[it] = pos + a; pos += a + b; }
      else if (a && rem == a) { pa[it] = pos; pb[it] = 0; pos = b; }
      else if (a && rem == b) { pb[it] = pos; pa[it] = 0; pos = a; }
      else { pa[it] = 0; pb[it] = a; pos = a + b; }
      if (g.a == A_LOC) pa[it] = 24 + 2 * k;
    }
    t.seg[sg] = (uint32_t)(g.n | g.nb << 6 | g.a << 9 | g.w << 11 | g.c0 << 13 | g.c1 << 16 | g.ks << 19 | g.dep << 22);
  }
  for (int i = 0; i < 2 * NST; i++) {
    int lag[2] = {8, 8};
    const int p[2] = {pa[i], pb[i]}, n[2] = {sa[i], sb[i]}, io = i % NST - o0;
    for (int x = 0; x < 2; x++) {
      for (int l = i < 8 ? i : 8; l >= 1; l--) {
        const int q[2] = {pa[i - l], pb[i - l]}, m[2] = {sa[i - l], sb[i - l]};
        for (int y = 0; y < 2; y++)
          if (n[x] && m[y] && p[x] < q[y] + m[y] && q[y] < p[x] + n[x]) lag[x] = l;
      }
      if (io > 0 && io < 8 && p[x] >= 20 && io - NOA < lag[x]) lag[x] = io - NOA;
    }
    if (i == NST + 3) lag[1] = 6;
    if (i < o0 && lag[0] < lag[1]) lag[1] = lag[0];
    t.ring[i] = (uint32_t)(pa[i] * 512 | lag[1] | lag[0] << 4 | pb[i] * 512 << 16);
  }
  int waits[2 * NST] = {};
  for (int i = 0; i < 2 * NST; i++)
    for (int x = 0; x < 2; x++) {
      const int j = i - (int)((t.ring[i] >> (4 * x)) & 15);
      if (j >= 0 && (!x || (i >= o0 && sa[i]))) waits[j]++;
    }
  for (int j = 0; j < 2 * NST - 8; j++)
    for (int x = 1; x >= 0; x--)
      for (int i = j + 7; i > j && !waits[j]; i--) {
        const int q = i - (int)((t.ring[i] >> (4 * x)) & 15);
        if (q < j && waits[q] > 1 && (!x || sa[i])) { waits[q]--; waits[j]++; t.ring[i] -= (uint32_t)(j - q) << (4 * x); }
      }
  for (int jc = 0; jc < 8; jc++)
    for (int ks = 0; ks < K_LIN; ks++)
      for (int i = 0; i < 8; i++) {
        const int u = i == jc ? 7 : i;
        t.seq[jc][ks] |= (uint32_t)(ks == K_L ? jc * 2 + (i & 1) : ks == K_OL ? 8 + jc : ks == K_OR ? 8 + u : u * 2 + (ks != K_E7)) << (4 * i);
      }
  t.seq[8][K_L] = 0x10; t.seq[8][K_E7] = 0x8765432; t.seq[8][K_O7] = 0xfedcba9;
  return t;
}

constexpr uint32_t RING0 = make_tabs().ring[0];

__device__ __forceinline__ bool elect_one() {
  uint32_t pred;
  asm volatile("{\n.reg .pred p;\nelect.sync _|p, 0xffffffff;\nselp.u32 %0, 1, 0, p;\n}" : "=r"(pred));
  return pred;
}

struct Ctx {
  const Params& p;
  uint32_t sb;
  uint32_t it;
  uint32_t lp;
  uint32_t ebar;
  bool rel;
  uint32_t da, db;
  int w, wg, wi, lane;
  int rb, jc;
  float m0, r0, m1, r1;
};
struct Stage { uint64_t da, db; };
struct Stats { float2 a, b, c, d; };

__device__ __forceinline__ uint32_t ld_tag_s(uint32_t sb) { return __float_as_uint(lds32f(sb + MISC_OFF + M_TAG)); }
__device__ __forceinline__ void carrive(const Ctx& c, uint32_t bar) {
  __syncwarp();
  if (c.lane == 0) mbar_arrive(c.sb + MISC_OFF + bar);
}

__device__ __forceinline__ Stage peek(const Ctx& c) {
  const uint32_t e = c.p.t.ring[c.it];
  Stage s;
  asm("mov.b64 %0, {%1, 0x40000040};" : "=l"(s.da) : "r"(c.da + (e & 0x3e00)));
  asm("mov.b64 %0, {%1, 0x40000040};" : "=l"(s.db) : "r"(c.db + (e >> 16)));
  return s;
}
__device__ __forceinline__ void wait_full(Ctx& c) {
  mbar_wait(c.sb + MISC_OFF + B_FULL + (c.it & 7) * 8, (c.it >> 3) & 1);
  c.it++;
}
__device__ __forceinline__ void release(Ctx& c) {
  if (c.rel) asm volatile("mbarrier.arrive.shared::cluster.b64 _, [%0];" ::"r"(c.ebar) : "memory");
  c.ebar = (c.ebar + 8) & ~64u;
}
__device__ __forceinline__ void load_stats(const Ctx& c, Stats& s) {
  const int lane = pin(c.lane);
  const float2* sp = c.p.s->stats + (lane & 3) * 2 * SEQ + pin(c.rb) * 128 + pin(c.w) * 16 + (lane >> 2);
  s.a = ld_b64(sp); s.b = ld_b64(sp + SEQ); s.c = ld_b64(sp + 8); s.d = ld_b64(sp + SEQ + 8);
}
__device__ __forceinline__ void combine2(float2 a, float2 b, float& mean, float& rstd) {
  mean = qsum(a.x + b.x) * 0.125f;
  const float d0 = a.x - mean, d1 = b.x - mean;
  const float m2 = qsum(a.y + b.y + 128.f * (d0 * d0 + d1 * d1));
  rstd = rsqrtf(m2 * (1.f / 1024.f) + 1e-5f);
}
__device__ __forceinline__ void combine_stats(Ctx& c, Stats& s, uint32_t tag) {
  uint32_t n = 0;
  while (true) {
    const uint32_t x = tag & 1, y = tag >> 1;
    const uint32_t bad = (__float_as_uint(s.a.x) ^ x) | (__float_as_uint(s.b.x) ^ x) | (__float_as_uint(s.c.x) ^ x) | (__float_as_uint(s.d.x) ^ x) |
                         (__float_as_uint(s.a.y) ^ y) | (__float_as_uint(s.b.y) ^ y) | (__float_as_uint(s.c.y) ^ y) | (__float_as_uint(s.d.y) ^ y);
    if (__all_sync(0xffffffffu, !(bad & 1))) break;
    if (++n > (1u << 18)) __trap();
    load_stats(c, s);
  }
  combine2(s.a, s.b, c.m0, c.r0);
  combine2(s.c, s.d, c.m1, c.r1);
}

template <bool INIT> __device__ __forceinline__ void mm(float (&A)[64], uint64_t da, uint64_t db) {
  if (INIT) wgmma_n128_init(A, da, db); else wgmma_n128(A, da, db);
}
template <bool INIT> __device__ __forceinline__ void mm(float (&A)[96], uint64_t da, uint64_t db) {
  if (INIT) wgmma_n192_init(A, da, db); else wgmma_n192(A, da, db);
}
__device__ __forceinline__ void keep(float& v) { asm volatile("" : "+f"(v)); }
__device__ __forceinline__ void keep(uint32_t& v) { asm volatile("" : "+r"(v)); }
template <int N> __device__ __forceinline__ void keep_all(float (&A)[N]) {
#pragma unroll
  for (int i = 0; i < N; i++) keep(A[i]);
}
__device__ __forceinline__ void cut(const Stage& s) {
  asm volatile("{\n.reg .pred p;\nsetp.eq.u32 p, %0, 0xffffffff;\n@p trap;\n}" ::"r"((uint32_t)s.db) : "memory");
}
struct Nop { __device__ __forceinline__ void operator()() const {} };
template <bool INIT, bool FIRST, int WAIT = 1, int N, class HOOK>
__device__ __forceinline__ void step1(Ctx& c, Stage& s, float (&A)[N], HOOK&& hook) {
  wait_full(c);
  wgmma_fence();
  mm<INIT>(A, s.da, s.db);
  if (!FIRST) {
    wgmma_commit();
    wgmma_wait<1>();
    release(c);
  }
  mm<false>(A, s.da + 2, s.db + 128);
  mm<false>(A, s.da + 4, s.db + 256);
  wgmma_commit();
  mm<false>(A, s.da + 6, s.db + 384);
  wgmma_commit();
  s = peek(c);
  if (sizeof(hook) > 1) cut(s);
  hook();
  if (WAIT == 2 || (WAIT == 1 && sizeof(hook) == 1)) wgmma_wait<1>();
}
template <bool INIT, int WAIT = 1, class HOOK>
__device__ __forceinline__ void step2(Ctx& c, Stage& s, float (&A)[64], float (&B)[64], HOOK&& hook) {
  wait_full(c);
  wgmma_fence();
  mm<INIT>(A, s.da, s.db);
  mm<INIT>(B, s.da, s.db + 1024);
  wgmma_commit();
  wgmma_wait<1>();
  release(c);
  mm<false>(A, s.da + 2, s.db + 128);
  mm<false>(B, s.da + 2, s.db + 1152);
  mm<false>(A, s.da + 4, s.db + 256);
  mm<false>(B, s.da + 4, s.db + 1280);
  wgmma_commit();
  mm<false>(A, s.da + 6, s.db + 384);
  mm<false>(B, s.da + 6, s.db + 1408);
  wgmma_commit();
  s = peek(c);
  if (sizeof(hook) > 1) cut(s);
  hook();
  if (WAIT == 2 || (WAIT == 1 && sizeof(hook) == 1)) wgmma_wait<1>();
}
template <bool INIT>
__device__ __forceinline__ void stage128(float (&A)[64], uint64_t da, uint64_t db) {
  mm<INIT>(A, da, db);
  mm<false>(A, da + 2, db + 128);
  mm<false>(A, da + 4, db + 256);
  mm<false>(A, da + 6, db + 384);
}

__device__ __forceinline__ uint32_t warp_rows(const Ctx& c) { return c.sb + STG_OFF + pin(c.w) * 2048; }
__device__ __forceinline__ uint32_t stg_base(uint32_t rows, int lane) {
  return rows + (lane & 15) * 128 + (((lane >> 4) ^ (lane & 7)) << 4);
}
__device__ __forceinline__ int seq_row(const Ctx& c, int r) {
  const int w = pin(c.w);
  return pin(c.rb) * 128 + (w & 3) * 32 + (w >> 2) + 2 * r;
}
template <int H>
__device__ __forceinline__ void resid_init(const Ctx& c, float (&A)[64]) {
  const uint32_t sta = stg_base(warp_rows(c), pin(c.lane)) + H * 16384;
#pragma unroll
  for (int b = 0; b < 8; b += 2) {
    uint32_t v0, v1, v2, v3;
    ldsm4(sta ^ (b << 4), v0, v1, v2, v3);
    float* a = A + H * 32 + 4 * b;
    a[0] = bf_lo(v0); a[1] = bf_hi(v0); a[2] = bf_lo(v1); a[3] = bf_hi(v1);
    a[4] = bf_lo(v2); a[5] = bf_hi(v2); a[6] = bf_lo(v3); a[7] = bf_hi(v3);
  }
#pragma unroll
  for (int i = 0; i < 32; i++) keep(A[H * 32 + i]);
}
__device__ __forceinline__ void stats_acc(const Ctx& c, int h, Stats& t) {
  const uint32_t sta = (stg_base(warp_rows(c), pin(c.lane)) ^ ((h & 1) << 6)) + (h >> 1) * 16384;
  uint32_t v[8];
#pragma unroll
  for (int b = 0; b < 2; b++) ldsm4(sta ^ (b << 5), v[4 * b], v[4 * b + 1], v[4 * b + 2], v[4 * b + 3]);
#pragma unroll
  for (int i = 0; i < 8; i += 2) {
    const float a = bf_lo(v[i]), b = bf_hi(v[i]), d = bf_lo(v[i + 1]), e = bf_hi(v[i + 1]);
    t.a.x += a + b; t.b.x = fmaf(a, a, fmaf(b, b, t.b.x));
    t.a.y += d + e; t.b.y = fmaf(d, d, fmaf(e, e, t.b.y));
  }
}
__device__ __forceinline__ void stats_store(const Ctx& c, const Stats& t, uint32_t tag) {
  const int lane = pin(c.lane), rh = lane & 1;
  float sum = (rh ? t.a.y : t.a.x) + __shfl_xor_sync(0xffffffffu, rh ? t.a.x : t.a.y, 1);
  float sq = (rh ? t.b.y : t.b.x) + __shfl_xor_sync(0xffffffffu, rh ? t.b.x : t.b.y, 1);
  sum += __shfl_xor_sync(0xffffffffu, sum, 2);
  sq += __shfl_xor_sync(0xffffffffu, sq, 2);
  const float mu = sum * (1.f / 128.f), m2 = fmaxf(fmaf(-mu, sum, sq), 0.f);
  if (!(lane & 2))
    st_b64(c.p.s->stats + pin(c.jc) * SEQ + pin(c.rb) * 128 + pin(c.w) * 16 + (lane >> 2) + rh * 8,
           (__float_as_uint(mu) & ~1u) | (tag & 1), (__float_as_uint(m2) & ~1u) | (tag >> 1));
}
__device__ __forceinline__ void store_box(const Ctx& c, __nv_bfloat16* g, int h) {
  const int lane = pin(c.lane), r = lane >> 3, ch = lane & 7;
  const uint32_t rows = warp_rows(c) + r * 128 + h * 16384;
  g += (size_t)seq_row(c, r) * DM + pin(c.jc) * 128 + h * 64 + ch * 8;
  uint4 v[4];
#pragma unroll
  for (int i = 0; i < 4; i++) v[i] = lds128(rows + i * 512 + ((ch ^ ((r + 4 * i) & 7)) << 4));
#pragma unroll
  for (int i = 0; i < 4; i++) stg128(g + i * 8 * DM, v[i].x, v[i].y, v[i].z, v[i].w);
}
template <int H>
__device__ __forceinline__ void stage_box(uint32_t sta, const float (&A)[64]) {
#pragma unroll
  for (int b = 8 * H; b < 8 * H + 8; b += 2)
    stsm4((sta ^ ((b & 7) << 4)) + H * 16384, pack_bf16(A[4 * b], A[4 * b + 1]), pack_bf16(A[4 * b + 2], A[4 * b + 3]),
          pack_bf16(A[4 * b + 4], A[4 * b + 5]), pack_bf16(A[4 * b + 6], A[4 * b + 7]));
}
__device__ __forceinline__ void finish_x(Ctx& c, float (&A)[64], __nv_bfloat16* g) {
  const uint32_t sta = stg_base(warp_rows(c), pin(c.lane));
  wgmma_wait<0>();
  release(c);
  if (c.it == 2 * NST) cluster_arrive();
  keep_all(A);
  stage_box<0>(sta, A);
  __syncwarp();
  store_box(c, g, 0);
  carrive(c, B_DONE + c.wg * 8);
  stage_box<1>(sta, A);
  fence_proxy_async_smem();
  carrive(c, B_BOX1);
  bar_sync(2 + c.wg, 128);
}

struct Att { uint32_t q[16], k[16], kp[8], p[2][4], vp[8], vf[16]; float s[2][3][4], v[4][2], o[8][4]; };
struct Cs { float4 v[4]; };
__device__ __forceinline__ uint32_t vswz(int r) { return ((r & 1) << 2) | ((r >> 1) & 3); }
__device__ __forceinline__ uint32_t kv_base(const Ctx& c) { return c.sb + KV_OFF + (pin(c.w) >> 2) * KV_WG; }
__device__ __forceinline__ uint4* halo_ptr(const Params& p, int lp, int s, int rb, int jc, int wg, int lane) {
  return p.s->halo + (size_t)((((lp * 2 + s) * 16 + rb) * 8 + jc) * 2 + wg) * (5 * 32) + lane;
}
__device__ __forceinline__ void load_cs(const Ctx& c, int i, Cs& cs) {
  const uint32_t a = c.sb + CSQ_OFF + i * 256 + (pin(c.lane) & 3) * 16;
#pragma unroll
  for (int j = 0; j < 4; j++) cs.v[j] = lds128f(a + j * 64);
}
template <int B, bool KEEP>
__device__ __forceinline__ void fix_box(const Ctx& c, float (&acc)[96], const Cs& cs) {
#pragma unroll
  for (int j = 0; j < 4; j++) {
    float* a = acc + 32 * B + 8 * j;
    a[0] -= c.m0 * cs.v[j].x; a[1] -= c.m0 * cs.v[j].y; a[2] -= c.m1 * cs.v[j].x; a[3] -= c.m1 * cs.v[j].y;
    a[4] -= c.m0 * cs.v[j].z; a[5] -= c.m0 * cs.v[j].w; a[6] -= c.m1 * cs.v[j].z; a[7] -= c.m1 * cs.v[j].w;
  }
#pragma unroll
  for (int i = 0; i < 32; i++) if (KEEP) keep(acc[32 * B + i]);
}
template <int B>
__device__ __forceinline__ void pack_box(const float (&acc)[96], uint32_t (&f)[16]) {
#pragma unroll
  for (int i = 0; i < 16; i++) { f[i] = pack_bf16(acc[32 * B + 2 * i], acc[32 * B + 2 * i + 1]); keep(f[i]); }
}
__device__ __forceinline__ void halo_send(const Ctx& c, int s, int part, uint32_t (&f)[16]) {
  uint4* hp = halo_ptr(c.p, c.lp, s, pin(c.rb), pin(c.jc), c.wg, pin(c.lane)) + part * 64;
  f[7] = f[7] ? f[7] : 0x8000u;
  f[15] = f[15] ? f[15] : 0x8000u;
  st_tag_if(c.wi == 3, hp, f[1], f[3], f[5], f[7]);
  st_tag_if(c.wi == 3, hp + 32, f[9], f[11], f[13], f[15]);
}
__device__ __forceinline__ void halo_clear(const Ctx& c, int s) {
  uint4* hp = halo_ptr(c.p, c.lp, s, pin(c.rb), pin(c.jc), c.wg, pin(c.lane));
#pragma unroll
  for (int i = 0; i < 4; i++) st_tag_if(c.wi == 3, hp + i * 32, 0u, 0u, 0u, 0u);
  if (!s) st_tag_if(c.wi == 3, hp + 128, __float_as_uint(c.r1), 1u, 1u, 1u);
}
__device__ __forceinline__ void put_k(const Ctx& c, const uint32_t (&k)[16]) {
  const uint32_t a = kv_base(c) + KV_K + 1024 + c.wi * 1024 + pin(c.lane) * 16;
  sts128(a, k[1], k[3], k[5], k[7]);
  sts128(a + 512, k[9], k[11], k[13], k[15]);
}
__device__ __forceinline__ void put_v(const Ctx& c, const uint32_t (&v)[16]) {
  const int lane = pin(c.lane), g = lane >> 2;
  const uint32_t a = kv_base(c) + (8 + c.wi * 16 + g) * 128 + (((lane & 3) ^ vswz(g)) << 4);
#pragma unroll
  for (int i = 0; i < 4; i++) {
    const int hh = i >> 1, rh = i & 1;
    sts128((a ^ (hh << 6)) + rh * 1024, v[8 * hh + rh], v[8 * hh + 2 + rh], v[8 * hh + 4 + rh], v[8 * hh + 6 + rh]);
  }
}
__device__ __forceinline__ void put_rstd(const Ctx& c) {
  const int lane = pin(c.lane);
  if (!(lane & 2)) sts32f(kv_base(c) + KV_R + (8 + c.wi * 16 + (lane & 1) * 8 + (lane >> 2)) * 4, (lane & 1) ? c.r1 : c.r0);
}
__device__ __forceinline__ void get_rstd(const Ctx& c, float (&rk)[4]) {
  const int lane = pin(c.lane), g = lane >> 2, j = 2 * (lane & 3);
  const uint32_t a = kv_base(c) + KV_R + (c.wi * 16 + j) * 4, a0 = a + (j <= g ? 32 : 0), a1 = a + (j + 1 <= g ? 36 : 4);
  rk[0] = lds32f(a0); rk[1] = lds32f(a1); rk[2] = lds32f(a0 + 32); rk[3] = lds32f(a1 + 32);
}
__device__ __forceinline__ void halo_wait(const Ctx& c, int s) {
  if (c.wi == 0) mbar_wait(c.sb + MISC_OFF + B_HALO + c.wg * 8, s);
}
__device__ __forceinline__ void att_ldk(const Ctx& c, Att& t) {
  const uint32_t a = kv_base(c) + KV_K + c.wi * 1024 + pin(c.lane) * 16;
  const uint4 u = lds128(a), v = lds128(a + 512);
  t.kp[0] = u.x; t.kp[1] = u.y; t.kp[2] = u.z; t.kp[3] = u.w; t.kp[4] = v.x; t.kp[5] = v.y; t.kp[6] = v.z; t.kp[7] = v.w;
}
template <int W>
__device__ __forceinline__ void att_ldv(const Ctx& c, Att& t) {
  const int lane = pin(c.lane);
  const uint32_t vb = kv_base(c) + c.wi * 2048, sw = vswz(lane & 7);
  if (W & 2) {
    const uint32_t ap = vb + (lane & 7) * 128 + (((lane >> 3) ^ sw) << 4);
    ldsm4t(ap, t.vp[0], t.vp[1], t.vp[2], t.vp[3]);
    ldsm4t(ap ^ 64, t.vp[4], t.vp[5], t.vp[6], t.vp[7]);
  }
  if (W & 1) {
    const uint32_t ao = vb + 1024 + (lane & 15) * 128 + (((lane >> 4) ^ sw) << 4);
#pragma unroll
    for (int b = 0; b < 8; b += 2) ldsm4t(ao ^ (b << 4), t.vf[2 * b], t.vf[2 * b + 1], t.vf[2 * b + 2], t.vf[2 * b + 3]);
  }
}
template <int W>
__device__ __forceinline__ void att_s(Att& t) {
#pragma unroll
  for (int ks = 0; ks < 2; ks++)
#pragma unroll
    for (int i = (W & 1) ? 0 : 4; i < ((W & 2) ? 6 : 4); i++) {
      const int hh = i & 1, kb = 2 - (i >> 1);
      const uint32_t* q = t.q + 8 * hh + 4 * ks;
      const uint32_t b0 = kb ? t.k[8 * hh + 4 * ks + kb - 1] : t.kp[4 * hh + 2 * ks], b1 = kb ? t.k[8 * hh + 4 * ks + kb + 1] : t.kp[4 * hh + 2 * ks + 1];
      if (ks) mma16816(t.s[hh][kb], q[0], q[1], q[2], q[3], b0, b1); else mma16816z(t.s[hh][kb], q[0], q[1], q[2], q[3], b0, b1);
    }
}
__device__ __forceinline__ void att_exp(const Ctx& c, Att& t, const float (&rk)[4]) {
  const int lane = pin(c.lane), g = lane >> 2, j = 2 * (lane & 3);
  const bool u0 = j <= g, u1 = j + 1 <= g, first = c.rb == 0 && c.wi == 0;
  const float sc = 0.17677669529663687f * 1.4426950408889634f;
  const float c0 = sc * c.r0, c1 = sc * c.r1;
  const float b0 = (first && !u0) ? -INFINITY : 0.f, b1 = (first && !u1) ? -INFINITY : 0.f;
  float m[4];
#pragma unroll
  for (int hh = 0; hh < 2; hh++) {
    t.v[2 * hh][0] = fmaf(u0 ? t.s[hh][1][0] : t.s[hh][0][0], c0 * rk[0], b0);
    t.v[2 * hh][1] = fmaf(u1 ? t.s[hh][1][1] : t.s[hh][0][1], c0 * rk[1], b1);
    t.v[2 * hh + 1][0] = (u0 ? t.s[hh][2][2] : t.s[hh][1][2]) * (c1 * rk[2]);
    t.v[2 * hh + 1][1] = (u1 ? t.s[hh][2][3] : t.s[hh][1][3]) * (c1 * rk[3]);
  }
#pragma unroll
  for (int i = 0; i < 4; i++) m[i] = fmaxf(t.v[i][0], t.v[i][1]);
#pragma unroll
  for (int o = 1; o <= 2; o <<= 1)
#pragma unroll
    for (int i = 0; i < 4; i++) m[i] = fmaxf(m[i], __shfl_xor_sync(0xffffffffu, m[i], o));
#pragma unroll
  for (int i = 0; i < 4; i++) {
    t.v[i][0] = ex2(t.v[i][0] - m[i]);
    t.v[i][1] = ex2(t.v[i][1] - m[i]);
    keep(t.v[i][0]);
    keep(t.v[i][1]);
  }
}
__device__ __forceinline__ void att_p(const Ctx& c, Att& t, const float (&rk)[4]) {
  const int lane = pin(c.lane), g = lane >> 2, j = 2 * (lane & 3);
  float m[4];
#pragma unroll
  for (int i = 0; i < 4; i++) m[i] = t.v[i][0] + t.v[i][1];
#pragma unroll
  for (int o = 1; o <= 2; o <<= 1)
#pragma unroll
    for (int i = 0; i < 4; i++) m[i] += __shfl_xor_sync(0xffffffffu, m[i], o);
  const uint32_t mu = (j <= g ? 0xffffu : 0u) | (j + 1 <= g ? 0xffff0000u : 0u);
#pragma unroll
  for (int i = 0; i < 4; i++) {
    const float inv = rcp(m[i]);
    const uint32_t pp = pack_bf16(t.v[i][0] * rk[2 * (i & 1)] * inv, t.v[i][1] * rk[2 * (i & 1) + 1] * inv);
    t.p[i >> 1][(i & 1) * 2] = pp & ~mu;
    t.p[i >> 1][(i & 1) * 2 + 1] = pp & mu;
    keep(t.p[i >> 1][(i & 1) * 2]);
    keep(t.p[i >> 1][(i & 1) * 2 + 1]);
  }
}
__device__ __forceinline__ void att_pv(Att& t) {
#pragma unroll
  for (int b = 0; b < 8; b++) mma1688z(t.o[b], t.p[b >> 2][0], t.vp[b]);
#pragma unroll
  for (int b = 0; b < 8; b++) mma16816(t.o[b], t.p[b >> 2][1], t.p[b >> 2][2], 0u, t.p[b >> 2][3], t.vf[2 * b], t.vf[2 * b + 1]);
}
template <bool LOCAL>
__device__ __forceinline__ void att_out(const Ctx& c, int s, const Att& t) {
  const int lane = pin(c.lane), g = lane >> 2, tq = lane & 3;
  __nv_bfloat16* dst = c.p.s->o + (size_t)seq_row(c, g) * DM + (s * 8 + pin(c.jc)) * 64 + tq * 8;
  const uint32_t la = warp_rows(c) + g * 128 + ((tq ^ g) << 4);
  uint32_t v[16];
#pragma unroll
  for (int i = 0; i < 4; i++) {
    const int hh = i & 1, rh = i >> 1;
#pragma unroll
    for (int b = 0; b < 4; b++) v[4 * i + b] = pack_bf16(t.o[4 * hh + b][2 * rh], t.o[4 * hh + b][2 * rh + 1]);
  }
#pragma unroll
  for (int i = 0; i < 4; i++) stg128(dst + (i >> 1) * 16 * DM + (i & 1) * 32, v[4 * i], v[4 * i + 1], v[4 * i + 2], v[4 * i + 3]);
  carrive(c, B_DONE + c.wg * 8);
  if (LOCAL) {
#pragma unroll
    for (int i = 0; i < 4; i++) sts128((la ^ ((i & 1) << 6)) + (i >> 1) * 1024, v[4 * i], v[4 * i + 1], v[4 * i + 2], v[4 * i + 3]);
  }
}
__device__ __forceinline__ void halo_go(const Ctx& c) {
  if (c.wi == 0 && c.lane == 0) mbar_arrive(c.sb + MISC_OFF + B_HGO + c.wg * 8);
}

__device__ __forceinline__ void phase_a(Ctx& c, Stage& s) {
  float O[64];
  const uint32_t misc = c.sb + MISC_OFF, stag = c.lp * 2 + 1;
  Att t;
  float rk[4];
  {
    float U[96], V[96];
    step1<true, true>(c, s, V, Nop());
    step1<false, false>(c, s, V, Nop());
    step1<true, false>(c, s, U, Nop());
    {
      Stats st;
      st.a = st.b = st.c = st.d = make_float2(0.f, 0.f);
#pragma unroll 1
      for (int k = 0; k < 11; k++)
        step1<false, false, 2>(c, s, U, [&]() {
          if (k == 2) mbar_wait(misc + B_XL, 0);
          if (k >= 3 && k < 7) stats_acc(c, k - 3, st);
          if (k == 6) stats_store(c, st, stag);
          if (k == 9) load_stats(c, st);
        });
      step1<false, false>(c, s, U, [&]() { combine_stats(c, st, stag); mbar_wait(misc + B_CSQ + 8, 0); });
    }
#pragma unroll 1
    for (int k = 0; k < 3; k++) {
      Cs cs;
      load_cs(c, 3 + k, cs);
      step1<false, false, 2>(c, s, U, [&]() {
        if (k & 2) { fix_box<2, true>(c, V, cs); mbar_wait(misc + B_CSQ, 0); }
        else if (k & 1) fix_box<1, true>(c, V, cs);
        else { halo_clear(c, 0); fix_box<0, true>(c, V, cs); }
      });
    }
    {
      Cs cs;
      load_cs(c, 1, cs);
      step1<false, false>(c, s, V, [&]() { keep_all(U); fix_box<1, false>(c, U, cs); pack_box<1>(U, t.k); halo_send(c, 0, 0, t.k); put_k(c, t.k); });
      step1<false, false>(c, s, V, [&]() { load_cs(c, 2, cs); fix_box<2, false>(c, U, cs); pack_box<2>(U, t.vf); halo_send(c, 0, 1, t.vf); put_v(c, t.vf); load_cs(c, 0, cs); halo_go(c); });
      step1<false, false>(c, s, V, [&]() { fix_box<0, false>(c, U, cs); pack_box<0>(U, t.q); put_rstd(c); });
    }
    step1<false, false>(c, s, V, [&]() { halo_clear(c, 1); });
    step1<false, false>(c, s, V, [&]() { bar_sync(2 + c.wg, 128); halo_wait(c, 0); att_ldk(c, t); get_rstd(c, rk); });
    att_s<3>(t);
    step1<false, false>(c, s, V, [&]() { att_exp(c, t, rk); });
    step1<false, false>(c, s, V, [&]() { att_ldv<3>(c, t); att_p(c, t, rk); });
    att_pv(t);
    step1<false, false>(c, s, V, [&]() { att_out<false>(c, 0, t); });
    step1<false, false>(c, s, V, [&]() { resid_init<0>(c, O); });
    step1<false, false>(c, s, V, [&]() { resid_init<1>(c, O); });
#pragma unroll 1
    for (int k = 0; k < 4; k++) step1<false, false>(c, s, V, Nop());
    wgmma_wait<0>();
    release(c);
    keep_all(V);
    pack_box<1>(V, t.k); halo_send(c, 1, 0, t.k); put_k(c, t.k);
    pack_box<2>(V, t.vf); halo_send(c, 1, 1, t.vf); put_v(c, t.vf);
    pack_box<0>(V, t.q);
  }
  step1<false, true, 2>(c, s, O, [&]() { halo_go(c); });
  step1<false, false>(c, s, O, Nop());
  wgmma_wait<0>();
  release(c);
  bar_sync(1, 256);
  cut(s);
  att_ldv<1>(c, t);
  att_s<1>(t);
  halo_wait(c, 1);
  att_ldk(c, t);
  att_ldv<2>(c, t);
  att_s<2>(t);
  att_exp(c, t, rk);
  att_p(c, t, rk);
  att_pv(t);
  att_out<true>(c, 1, t);
  bar_sync(1, 256);
  step1<false, true>(c, s, O, Nop());
#pragma unroll 1
  for (int k = NOA + 1; k < 16; k++)
    step1<false, false, 2>(c, s, O, [&]() {
      if (k == 6) { fence_proxy_async_smem(); bar_sync(2 + c.wg, 128); }
    });
  finish_x(c, O, c.p.s->x);
}

template <int H>
__device__ __forceinline__ void scale_to(const Ctx& c, float (&E)[64], float (&A)[64]) {
  const float h0 = 0.5f * c.r0, h1 = 0.5f * c.r1;
#pragma unroll
  for (int i = (H & 1) ? 0 : 32; i < ((H & 2) ? 64 : 32); i++) {
    keep(A[i]);
    E[i] = A[i] * (i < 32 ? ((i & 2) ? h1 : h0) : ((i & 2) ? c.r1 : c.r0));
    keep(E[i]);
  }
}
template <int B>
__device__ __forceinline__ void piece(const Ctx& c, float (&A)[64], const float4 cs) {
  float h[4];
#pragma unroll
  for (int e = 0; e < 4; e++) {
    const float n = (e & 2) ? c.m1 : c.m0;
    const float a = fmaf(n, (e & 1) ? cs.y : cs.x, A[4 * B + e]), u = fmaf(n, (e & 1) ? cs.w : cs.z, A[32 + 4 * B + e]);
    const float w = a * u;
    h[e] = fmaf(w, tanh_approx(a), w);
  }
  A[4 * B] = __uint_as_float(pack_bf16(h[0], h[1]));
  A[4 * B + 1] = __uint_as_float(pack_bf16(h[2], h[3]));
  if (B == 7) carrive(c, B_CSFREE);
}
template <int B>
__device__ __forceinline__ void piece2(const Ctx& c, float (&E)[64], const float4 c0, const float4 c1) {
  piece<B>(c, E, c0);
  piece<B + 1>(c, E, c1);
}
template <int Q>
__device__ __forceinline__ void store_h2(const Ctx& c, const float (&E)[64], int blk) {
  const int lane = pin(c.lane);
  __nv_bfloat16* dst = c.p.s->h + (size_t)seq_row(c, lane >> 2) * FF + (blk * 8 + pin(c.jc)) * 64 + Q * 32 + (lane & 3) * 8;
#pragma unroll
  for (int rh = 0; rh < 2; rh++)
    stg128(dst + rh * 16 * FF, __float_as_uint(E[16 * Q + rh]), __float_as_uint(E[16 * Q + 4 + rh]),
           __float_as_uint(E[16 * Q + 8 + rh]), __float_as_uint(E[16 * Q + 12 + rh]));
}
__device__ __forceinline__ void tail_piece(const Ctx& c, float (&A)[64], const float4 cs, int k, int blk) {
  if (k < 4) {
    if (k < 2) { if (k == 0) piece<0>(c, A, cs); else piece<1>(c, A, cs); }
    else { if (k == 2) piece<2>(c, A, cs); else { piece<3>(c, A, cs); store_h2<0>(c, A, blk); } }
  } else {
    if (k < 6) { if (k == 4) piece<4>(c, A, cs); else piece<5>(c, A, cs); }
    else { if (k == 6) piece<6>(c, A, cs); else { piece<7>(c, A, cs); store_h2<1>(c, A, blk); } }
  }
}
template <int LOFF>
__device__ __forceinline__ void drain(Ctx& c, Stage& s, float (&L)[64], float (&M)[64], float (&E)[64]) {
  wait_full(c);
  wgmma_fence();
  stage128<false>(M, s.da, s.db + (1024 - LOFF));
  wgmma_commit();
  wgmma_wait<1>();
  release(c);
  scale_to<3>(c, E, L);
  wgmma_fence();
  stage128<true>(L, s.da, s.db + LOFF);
  wgmma_commit();
  s = peek(c);
}
__device__ __forceinline__ void phase_b(Ctx& c, Stage& s) {
  float X[64], Y[64], E[64];
  const uint32_t stag = (c.lp * 2 + 2) & 3;
  step1<true, true>(c, s, X, Nop());
  step1<false, false>(c, s, X, Nop());
  {
    Stats st;
    st.a = st.b = st.c = st.d = make_float2(0.f, 0.f);
    step2<true>(c, s, E, Y, Nop());
#pragma unroll 1
    for (int k = 0; k < 8; k++)
      step2<false, 2>(c, s, E, Y, [&]() {
        if (k < 4) stats_acc(c, k, st);
        if (k == 3) stats_store(c, st, stag);
        if (k == 5) load_stats(c, st);
        if (k == 7) { combine_stats(c, st, stag); c.m0 *= -c.r0; c.m1 *= -c.r1; }
      });
  }
#pragma unroll 1
  for (int k = 0; k < 7; k++) step1<false, false>(c, s, E, Nop());
  step2<false, 0>(c, s, X, Y, [&]() { scale_to<3>(c, E, E); });
#pragma unroll 1
  for (int blk = 0;; blk++) {
    mbar_wait(c.sb + MISC_OFF + B_CS, (blk + c.lp) & 1);
    const int n = blk == 2 ? 8 : 6;
#pragma unroll 1
    for (int k = 0; k < n; k++) {
      const uint32_t ca = c.sb + CSG_OFF + (k & 3) * 128 + (pin(c.lane) & 3) * 16;
      const float4 c0 = lds128f(ca), c1 = lds128f(ca + 64);
      step2<false, 2>(c, s, X, Y, [&]() {
        if (k & 4) {
          if (!(k & 3)) store_h2<0>(c, E, blk);
          else if (k == 5) { store_h2<1>(c, E, blk); if (blk == 3) carrive(c, B_DONE + c.wg * 8); }
        } else if (k & 2) {
          if (k & 1) piece2<6>(c, E, c0, c1); else piece2<4>(c, E, c0, c1);
        } else {
          if (k & 1) piece2<2>(c, E, c0, c1); else piece2<0>(c, E, c0, c1);
        }
      });
    }
    if (blk == 4) break;
    if (blk & 1) drain<0>(c, s, X, Y, E); else drain<1024>(c, s, Y, X, E);
  }
  step2<false>(c, s, X, Y, [&]() { resid_init<0>(c, E); });
  step2<false>(c, s, X, Y, [&]() { resid_init<1>(c, E); mbar_wait(c.sb + MISC_OFF + B_CS, (5 + c.lp) & 1); });
  step1<false, false>(c, s, X, [&]() { scale_to<1>(c, Y, Y); });
  step1<false, false>(c, s, X, [&]() { scale_to<2>(c, Y, Y); });
#pragma unroll 1
  for (int blk = 5;; blk++) {
#pragma unroll 1
    for (int k = 0; k < 8; k++) {
      const float4 cs = lds128f(c.sb + CSG_OFF + k * 64 + (pin(c.lane) & 3) * 16);
      if (blk == 5 && k < 5) step1<false, false, 0>(c, s, X, Nop()); else step1<false, false, 0>(c, s, E, Nop());
      tail_piece(c, Y, cs, k, blk);
      wgmma_wait<1>();
    }
    if (blk == 6) break;
    step1<false, false>(c, s, E, [&]() { scale_to<1>(c, Y, X); });
    step1<false, false>(c, s, E, [&]() { scale_to<2>(c, Y, X); mbar_wait(c.sb + MISC_OFF + B_CS, c.lp & 1); });
  }
  carrive(c, B_DONE + c.wg * 8);
#pragma unroll 1
  for (int k = 0; k < 43; k++) step1<false, false>(c, s, E, Nop());
  finish_x(c, E, c.lp ? c.p.out : c.p.s->x);
}

__device__ __forceinline__ void acc8(float (&a)[8], const uint4& v) {
  a[0] += bf_lo(v.x); a[1] += bf_hi(v.x); a[2] += bf_lo(v.y); a[3] += bf_hi(v.y);
  a[4] += bf_lo(v.z); a[5] += bf_hi(v.z); a[6] += bf_lo(v.w); a[7] += bf_hi(v.w);
}
__device__ __forceinline__ void st_sums(uint4* dst, const float (&a)[8], uint32_t tag) {
  uint32_t u[8];
#pragma unroll
  for (int i = 0; i < 8; i++) u[i] = (__float_as_uint(a[i]) & ~1u) | ((tag >> (i & 3)) & 1u);
  st_tag(dst, u[0], u[1], u[2], u[3]);
  st_tag(dst + 1, u[4], u[5], u[6], u[7]);
}
__device__ __forceinline__ bool add_sum(float4& a, const uint4& v, uint32_t tag) {
  a.x += __uint_as_float(v.x & ~1u); a.y += __uint_as_float(v.y & ~1u);
  a.z += __uint_as_float(v.z & ~1u); a.w += __uint_as_float(v.w & ~1u);
  return ((v.x & 1) | (v.y & 1) << 1 | (v.z & 1) << 2 | (v.w & 1) << 3) == (tag & 15);
}

__device__ __forceinline__ void spare_sum(const Params& p, uint32_t sb, int d, int w, int lane) {
  const int chunk = (w & 1) * 4 + (lane & 3), rg = lane >> 2;
  const uint32_t base = sb + (w >> 1) * 8192 + rg * 128 + ((chunk ^ rg) << 4);
  uint32_t slot = 0, par = 0;
#pragma unroll 1
  for (int t = d; t < 28; t += 4) {
    float a[8] = {0, 0, 0, 0, 0, 0, 0, 0};
#pragma unroll 1
    for (int k = 0; k < 16; k++) {
      mbar_wait_idle(sb + MISC_OFF + B_SFULL + slot * 8, par);
      uint4 v[8];
#pragma unroll
      for (int r = 0; r < 8; r++) v[r] = lds128(base + slot * 32768 + r * 1024);
#pragma unroll
      for (int r = 0; r < 8; r++) acc8(a, v[r]);
      __syncwarp();
      if (lane == 0) mbar_arrive(sb + MISC_OFF + B_SEMPTY + slot * 8);
      if (++slot == 6) { slot = 0; par ^= 1; }
    }
#pragma unroll 1
    for (int o = 16; o >= 4; o >>= 1)
#pragma unroll
      for (int i = 0; i < 8; i++) a[i] += __shfl_xor_sync(0xffffffffu, a[i], o);
    if (lane < 4) st_sums(p.s->part + (3 * DM + ((w >> 1) & 1) * FF + t * 128 + (w >> 2) * 64 + (w & 1) * 32) / 4 + lane * 2, a, ld_tag_s(sb));
  }
}
__device__ __forceinline__ void spare_load(const Params& p, uint32_t sb, int d, int lane) {
  uint32_t slot = 0, par = 1;
  const uint32_t want = ld_epoch(p) * 2 + 1, t0 = clock();
  while ((uint32_t)clock() - t0 < 13000) __nanosleep(200);
#pragma unroll 1
  for (int t = d; t < 28; t += 4) {
    if ((t >> 2) == 2) {
#pragma unroll 1
      for (uint32_t i = 0, n = 0; i < 4;) {
        const uint32_t v = ld_flag(reinterpret_cast<const uint8_t*>(p.s->flags + (i * 4 + (lane >> 3)) * 8 + F_X1B - 1) + (lane & 7) * 2);
        if (__all_sync(0xffffffffu, ((v - want) & 255) < 2)) i++; else __nanosleep(300);
        if (++n > (1u << 20)) __trap();
      }
    }
#pragma unroll 1
    for (int k = 0; k < 16; k++) {
      const uint32_t bar = sb + MISC_OFF + B_SFULL + slot * 8;
      mbar_wait(sb + MISC_OFF + B_SEMPTY + slot * 8, par);
      if (elect_one()) {
        mbar_expect_tx(bar, 32768);
#pragma unroll
        for (int b = 0; b < 4; b++) tma_load(sb + slot * 32768 + b * 8192, (b & 1) ? &p.wu : &p.wg, bar, t * 128 + (b >> 1) * 64, k * 64);
      }
      if (++slot == 6) { slot = 0; par ^= 1; }
    }
  }
}
__device__ __forceinline__ uint32_t qkv_sums(const Params& p, uint32_t sb, int q, int rb, int jc, int lane) {
  const uint32_t bar = sb + MISC_OFF + B_SLAB + q * 8, buf = sb + KV_OFF + q * 8192;
  const uint32_t tag = ld_epoch(p) + 1;
  mbar_wait_idle(sb + MISC_OFF + B_FULL, 0);
  const uint32_t t0 = clock();
  if (q == 0) {
    const int gx = (jc >> 1) - 1;
    if (gx >= 0) mbar_wait_idle(sb + MISC_OFF + B_EMPTY + gx * 8, 0);
    if (elect_one()) {
      mbar_expect_tx(sb + MISC_OFF + B_XL, 32768);
      tma_load3(sb + STG_OFF, &p.x0, sb + MISC_OFF + B_XL, jc * 128, rb * 64);
      tma_load3(sb + STG_OFF + 16384, &p.x0, sb + MISC_OFF + B_XL, jc * 128 + 64, rb * 64);
    }
  }
  {
    const int col = q * DM + ((rb & 1) * 8 + jc) * 64;
    float a[8] = {0.f, 0.f, 0.f, 0.f, 0.f, 0.f, 0.f, 0.f};
#pragma unroll 1
    for (int h = 0; h < 2; h++) {
      while (h && (uint32_t)clock() - t0 < 4600) __nanosleep(100);
      if (elect_one()) {
        mbar_expect_tx(bar, 8192);
        tma_load(buf, &p.wqkv, bar, col, ((rb & 14) + h) * 64);
        tma_load(buf + 4096, &p.wqkv, bar, col, ((rb & 14) + h) * 64 + 32);
      }
      mbar_wait_idle(bar, h);
      const uint32_t base = buf + (lane >> 3) * 128 + (((lane & 7) ^ (lane >> 3)) << 4);
#pragma unroll 1
      for (int r = 0; r < 8; r += 2) {
        const uint4 v0 = lds128(base + r * 1024), v1 = lds128((base ^ 64) + r * 1024 + 512);
        const uint4 v2 = lds128(base + r * 1024 + 1024), v3 = lds128((base ^ 64) + r * 1024 + 1536);
        acc8(a, v0); acc8(a, v1); acc8(a, v2); acc8(a, v3);
      }
      fence_proxy_async_smem();
      __syncwarp();
    }
#pragma unroll 1
    for (int o = 8; o <= 16; o <<= 1)
#pragma unroll
      for (int j = 0; j < 8; j++) a[j] += __shfl_xor_sync(0xffffffffu, a[j], o);
    if (lane < 8) st_sums(p.s->part + ((rb >> 1) * NCS + col) / 4 + lane * 2, a, tag);
  }
#pragma unroll 1
  for (int s = 1; s >= 0; s--) {
    const uint4* src = p.s->part + ((lane >> 4) * 4 * NCS + q * DM + (s * 8 + jc) * 64) / 4 + (lane & 15);
    float4 a;
    uint32_t n = 0;
    while (true) {
      uint4 v[4];
#pragma unroll
      for (int r = 0; r < 4; r++) v[r] = ld_tag(src + r * (NCS / 4));
      a = make_float4(0.f, 0.f, 0.f, 0.f);
      bool ok = true;
#pragma unroll
      for (int r = 0; r < 4; r++) ok = add_sum(a, v[r], tag) && ok;
      if (__all_sync(0xffffffffu, ok)) break;
      if (++n > (1u << 18)) __trap();
    }
    a.x += __shfl_xor_sync(0xffffffffu, a.x, 16); a.y += __shfl_xor_sync(0xffffffffu, a.y, 16);
    a.z += __shfl_xor_sync(0xffffffffu, a.z, 16); a.w += __shfl_xor_sync(0xffffffffu, a.w, 16);
    const uint32_t dst = sb + CSQ_OFF + (s * 3 + q) * 256 + ((lane & 15) >> 2) * 64 + (lane & 1) * 32 + (lane & 2) * 4 + (lane >> 4) * 16;
    sts64f(dst, lane < 16 ? a.x : a.z, lane < 16 ? a.y : a.w);
    __syncwarp();
    if (lane == 0) mbar_arrive(sb + MISC_OFF + B_CSQ + s * 8);
  }
  return tag;
}

struct Prod {
  const Params& p;
  uint32_t sb, it;
  uint32_t seq, kb, kinc;
};
__device__ __forceinline__ uint32_t seg_begin(Prod& pr, int sg, int jc) {
  const uint32_t d = pr.p.t.seg[sg], ks = (d >> 19) & 7;
  pr.seq = pr.p.t.seq[sg < 6 ? 8 : jc][ks];
  pr.kinc = ks == K_LIN;
  pr.kb = ks == K_LIN ? ((d >> 13) & 7) * 8 : 0;
  return d;
}
__device__ __forceinline__ int next_k(Prod& pr) {
  const int k = (pr.kb + (pr.seq & 15)) * 64;
  pr.seq >>= 4;
  pr.kb += pr.kinc;
  return k;
}
__device__ __forceinline__ void wait_released(const Prod& pr, uint32_t lag) {
  const uint32_t j = pr.it - lag;
  mbar_wait(pr.sb + MISC_OFF + B_EMPTY + (j & 7) * 8, (j >> 3) & 1);
}
template <int NB>
__device__ __forceinline__ void produce_b(Prod& pr, int n, uint32_t bytes, const CUtensorMap* tb, int c0, int c1, uint32_t rank,
                                          const CUtensorMap* ta, int arow) {
#pragma unroll 1
  for (; n > 0; n--) {
    const uint32_t e = pr.p.t.ring[pr.it];
    const int k = pin(next_k(pr));
    const uint32_t bar = pin(pr.sb + MISC_OFF + B_FULL + (pr.it & 7) * 8);
    const uint32_t b = pin(pr.sb + ((e >> 16) << 4) + rank * (NB == 3 ? 4096 : 8192));
    wait_released(pr, e & 15);
    if (elect_one()) {
      mbar_expect_tx(bar, bytes);
      if (NB == 3) {
#pragma unroll
        for (int q = 0; q < 3; q++) tma_load_mc(b + q * 8192, tb, bar, q * DM + c0, k + rank * 32);
        if (ta) tma_load3(pr.sb + ((e & 0x3e00) << 4), ta, bar, k, arow);
      } else if (NB == 5) {
        tma_load5_mc(b, tb, bar, c0, k >> 5);
      } else {
        tma_load_mc(b, tb, bar, c0, k);
        if (NB == 4) tma_load_mc(b + 16384, tb, bar, c1, k);
      }
    }
    pr.it++;
  }
}
__device__ __forceinline__ void cs_fill(const Params& p, uint32_t sb, int i, int jc, int lane, uint32_t tag) {
  const int blk = i >= 7 ? i - 7 : i, m = lane & 15;
  const uint4* src = p.s->part + (3 * DM + (lane >> 4) * FF + (blk * 8 + jc) * 64) / 4 + m;
  float4 a;
  uint32_t n = 0;
  while (true) {
    a = make_float4(0.f, 0.f, 0.f, 0.f);
    if (__all_sync(0xffffffffu, add_sum(a, ld_tag(src), tag))) break;
    if (++n > (1u << 18)) __trap();
    __nanosleep(500);
  }
  if (i > 0) mbar_wait_idle(sb + MISC_OFF + B_CSFREE, (i - 1) & 1);
  const float f = lane < 16 ? 0.5f : 1.f;
  const uint32_t dst = sb + CSG_OFF + m * 32 + (lane >> 4) * 8;
  sts64f(dst, a.x * f, a.y * f);
  sts64f(dst + 16, a.z * f, a.w * f);
  __syncwarp();
  if (lane == 0) mbar_arrive(sb + MISC_OFF + B_CS);
}

template <bool BY_SM>
__global__ void __cluster_dims__(2, 1, 1) __launch_bounds__(384, 1)
fused_kernel(const __grid_constant__ Params p) {
  extern __shared__ __align__(1024) uint8_t smem_raw[];
  const uint32_t sb = smem_u32(smem_raw);
  const uint32_t misc = sb + MISC_OFF;
  const int warp = __shfl_sync(0xffffffffu, threadIdx.x >> 5, 0), lane = threadIdx.x & 31;
  uint32_t smid;
  asm volatile("mov.u32 %0, %%smid;" : "=r"(smid));
  const int tpc = smid >> 1;
  const int cl = __shfl_sync(0xffffffffu, !BY_SM ? (int)blockIdx.x >> 1 : tpc < 32 ? tpc
                           : tpc < 60 ? (4 + (tpc - 32) / 7) * 8 + 1 + (tpc - 32) % 7 : tpc < 62 ? tpc + 4 : (tpc - 58) * 8, 0);
  const uint32_t rank = blockIdx.x & 1;
  const int cta = cl * 2 + rank;
  const bool spare = cta >= NCTA;
  const int rb = (7 - (cl & 7)) * 2 + rank, jc = (cl >> 3) & 7;

  if (warp < 8) {
    if (warp < 2 && elect_one()) asm volatile("prefetch.tensormap [%0];" ::"l"(warp ? &p.x0 : &p.wqkv) : "memory");
    cluster_arrive();
    uint32_t tag = ld_epoch(p) + 1;
    cluster_wait();
    asm volatile("setmaxnreg.inc.sync.aligned.u32 232;");
    asm volatile("st.shared.u32 [%0], %1;" ::"r"(misc + M_TAG), "r"(tag) : "memory");
    if (spare) {
      spare_sum(p, sb, cta - NCTA, warp, lane);
      cluster_arrive();
    } else {
      Ctx c{p};
      c.sb = sb; c.w = warp; c.wg = warp >> 2; c.wi = warp & 3; c.lane = lane; c.rb = rb; c.jc = jc;
      c.rel = c.wi == 0 && lane < 2;
      asm("mapa.shared::cluster.u32 %0, %1, %2;" : "=r"(c.ebar) : "r"(misc + B_EMPTY), "r"(lane & 1));
      c.da = (((sb + c.wg * 8192) & 0x3FFFF) >> 4) | (1u << 16);
      c.db = ((sb & 0x3FFFF) >> 4) | ((8192u >> 4) << 16);
      c.it = 0;
      Stage s = peek(c);
#pragma unroll 1
      for (c.lp = 0; c.lp < 2; c.lp++) {
        phase_a(c, s);
        phase_b(c, s);
      }
      store_box(c, p.out, 1);
    }
  } else {
    asm volatile("setmaxnreg.dec.sync.aligned.u32 40;");
    if (elect_one()) {
      if (warp == 10) {
        for (int i = 0; i < 8; i++) mbar_init(misc + B_FULL + i * 8, 1);
      } else if (warp == 9) {
        if (sb & 1023) __trap();
        for (int i = 0; i < 8; i++) mbar_init(misc + B_EMPTY + i * 8, 4);
      } else if (warp == 8) {
        for (int i = 0; i < 2; i++) { mbar_init(misc + B_DONE + i * 8, 4); mbar_init(misc + B_HGO + i * 8, 1); mbar_init(misc + B_HALO + i * 8, 1); mbar_init(misc + B_CSQ + i * 8, 3); }
        mbar_init(misc + B_CS, 1); mbar_init(misc + B_XL, 1); mbar_init(misc + B_BOX1, 8); mbar_init(misc + B_CSFREE, 8);
      } else {
        for (int i = 0; i < 6; i++) { mbar_init(misc + B_SFULL + i * 8, 1); mbar_init(misc + B_SEMPTY + i * 8, 8); }
      }
      asm volatile("fence.mbarrier_init.release.cluster;" ::: "memory");
    }
    cluster_arrive();
    if (warp == 10 && !spare && elect_one()) {
      mbar_expect_tx(misc + B_FULL, 40960);
      tma_load3(sb + ((RING0 & 0x3e00) << 4), &p.x0, misc + B_FULL, 0, rb * 64);
#pragma unroll
      for (int i = 0; i < 6; i++) tma_load(sb + ((RING0 >> 16) << 4) + i * 4096, &p.wqkv, misc + B_FULL, (i >> 1) * DM + (8 + jc) * 64, (i & 1) * 32);
#pragma unroll 1
      for (int i = 1; i < 4; i++) tma_load3(sb + ((p.t.ring[i] & 0x3e00) << 4), &p.x0, misc + B_FULL + i * 8, (i & 1) * 64, rb * 64);
    }
    cluster_wait();
    if (spare) {
      if (warp == 8) {
        spare_load(p, sb, cta - NCTA, lane);
      }
    } else if (warp == 8) {
      Prod pr{p};
      pr.sb = sb; pr.it = 0;
#pragma unroll 1
      for (int sg = 0; sg < 2 * NSEG; sg++) {
        const uint32_t d = seg_begin(pr, sg, jc);
        if (sg == 0) { pr.seq >>= 4; pr.it = 1; }
        const int n = (d & 63) - (sg == 0), nb = (d >> 6) & 7, am = (d >> 9) & 3, wm = (d >> 11) & 3;
        const CUtensorMap* tb = &p.wqkv + (wm == W_D ? 4 : wm == W_G ? 2 + rank : wm);
        const int c0 = (wm & 1) ? jc * 128 + rank * 64 : (((d >> 13) & 7) * 8 + jc) * 64, c1 = (((d >> 16) & 7) * 8 + jc) * 64;
        const uint32_t bytes = nb * 8192 + (am ? 16384 : 0);
        if (nb == 3) produce_b<3>(pr, n, bytes, tb, c0, c1, rank, sg < 6 && sg > 1 ? &p.x0 : nullptr, rb * 64);
        else if (nb == 4) produce_b<4>(pr, n, bytes, tb, c0, c1, rank, nullptr, 0);
        else if (wm == W_D) produce_b<5>(pr, n, bytes, tb, c0, c1, rank, nullptr, 0);
        else produce_b<2>(pr, n, bytes, tb, c0, c1, rank, nullptr, 0);
      }
    } else {
      const uint32_t tag = qkv_sums(p, sb, warp - 9, rb, jc, lane);
      if (warp == 10) {
        Prod pr{p};
        pr.sb = sb; pr.it = 32;
        const uint8_t* fl = reinterpret_cast<const uint8_t*>(p.s->flags + rb * 8) + (lane & 15);
        mbar_wait_idle(misc + B_DONE, 0);
        uint32_t early = ~0u;
#pragma unroll 1
        for (int sg = 6; sg < 2 * NSEG; sg++) {
          const uint32_t d = seg_begin(pr, sg, jc), dep = d >> 22, am = (d >> 9) & 3;
          if (!am) { pr.it += d & 63; early = ~0u; continue; }
          const uint32_t want = (tag * 2 - (sg < NSEG)) & 255;
          uint32_t ready = dep ? __ballot_sync(0xffffffffu, early == want) : ~0u;
          if (dep) fence_proxy_async();
#pragma unroll 1
          for (int n = d & 63; n > 0; n--) {
            const uint32_t e = pr.p.t.ring[pr.it];
            const int k = pin(next_k(pr));
            const uint32_t bar = pin(misc + B_FULL + (pr.it & 7) * 8), a = pin(sb + ((e & 0x3e00) << 4));
            if (n == 1 && (pr.p.t.seg[sg + 1] >> 22)) early = ld_flag(fl + ((pr.p.t.seg[sg + 1] >> 22) - 1) * 16);
            if (am == A_X) wait_released(pr, (e >> 4) & 15);
            if (ready != ~0u) {
              const uint32_t need = (am == A_H || n == 1) ? ~0u : 3u << (am == A_X ? (k >> 6) & 14 : (k >> 5) & 14);
              if ((ready & need) != need) {
                const uint8_t* f = fl + (dep - 1) * 16;
                uint32_t v0 = ld_flag(f);
                const uint32_t t0 = clock();
                while ((uint32_t)clock() - t0 < 120) {}
                for (uint32_t i = 0;; i++) {
                  const uint32_t v1 = ld_flag(f);
                  ready = __ballot_sync(0xffffffffu, v0 == want);
                  if ((ready & need) == need) break;
                  v0 = ld_flag(f);
                  ready = __ballot_sync(0xffffffffu, v1 == want);
                  if ((ready & need) == need) break;
                  if (i > (1u << 19)) __trap();
                }
                fence_proxy_async();
              }
            }
            if (am != A_X) wait_released(pr, (e >> 4) & 15);
            if (elect_one()) tma_load3(a, &p.x0 + am, bar, k, rb * 64);
            pr.it++;
          }
        }
      } else {
        const int w = (warp - 9) >> 1;
        int ncs = 0;
#pragma unroll 1
        for (int ev = 0; ev < 14; ev++) {
          const int layer = ev >> 3, e = ev & 7;
          if (e < 2) {
            uint4* hp = halo_ptr(p, layer, e, rb - 1, jc, w, pin(lane));
            mbar_wait_idle(misc + B_HGO + w * 8, e);
            uint4 v[5];
            uint32_t n = 0;
#pragma unroll
            for (int i = 0; i < 5; i++) v[i] = make_uint4(0, 0, 0, 0);
            while (rb > 0) {
#pragma unroll
              for (int i = 0; i < 4; i++) v[i] = ld_tag(hp + i * 32);
              if (!e) v[4] = ld_tag(hp + 128);
              if (__all_sync(0xffffffffu, v[0].w && v[1].w && v[2].w && v[3].w && (e || v[4].w))) break;
              if (++n > (1u << 18)) __trap();
            }
            const int l = pin(lane);
            const uint32_t kv = sb + KV_OFF + w * KV_WG, d0 = kv + (l >> 2) * 128 + (((l & 3) ^ vswz(l >> 2)) << 4);
            sts128(kv + KV_K + l * 16, v[0].x, v[0].y, v[0].z, v[0].w);
            sts128(kv + KV_K + 512 + l * 16, v[1].x, v[1].y, v[1].z, v[1].w);
            sts128(d0, v[2].x, v[2].y, v[2].z, v[2].w);
            sts128(d0 ^ 64, v[3].x, v[3].y, v[3].z, v[3].w);
            if (!e) sts32f(kv + KV_R + (l >> 2) * 4, __uint_as_float(v[4].x));
            __syncwarp();
            if (lane == 0) mbar_arrive(misc + B_HALO + w * 8);
          }
          if (w == 1) {
            const int c1 = ev == 2 ? 1 : e == 4 ? 5 + 7 * layer : e == 5 ? 8 + 6 * layer : 0;
#pragma unroll 1
            for (; ncs < c1; ncs++) cs_fill(p, sb, ncs, jc, lane, tag);
          }
          uint8_t* flag = reinterpret_cast<uint8_t*>(p.s->flags + rb * 8 + e) + jc * 2 + w;
          if ((e & 3) == 3) {
            if (w == 0 && lane == 0) {
              mbar_wait(misc + B_BOX1, (ev >> 2) & 1);
              mbar_wait(misc + B_FULL + 4 * 8, ev > 3);
              tma_store3(&p.x, sb + STG_OFF + 16384, jc * 128 + 64, rb * 64);
              fence_gpu();
              st_flag(flag, tag * 2 - (ev < 6));
              st_flag(flag + 1, tag * 2 - (ev < 6));
            }
            continue;
          }
          mbar_wait_idle(misc + B_DONE + w * 8, (ev - (ev >> 2)) & 1);
          if (lane == 0) {
            fence_gpu();
            st_flag(flag, tag * 2 - (ev < 6));
          }
          if (e < 2 && rb > 0) {
            __syncwarp();
            uint4* hp = halo_ptr(p, layer, e, rb - 1, jc, w, pin(lane));
#pragma unroll 1
            for (int i = 0; i < 5; i++) st_tag(hp + i * 32, 0u, 0u, 0u, 0u);
          }
        }
      }
    }
    __syncwarp();
    if (BY_SM) {
      uint32_t nsmid;
      asm volatile("mov.u32 %0, %%nsmid;" : "=r"(nsmid));
      if (nsmid != 132) __trap();
    }
    if (threadIdx.x == 256) p.s->epoch[blockIdx.x] = ld_tag_s(sb);
    cluster_arrive();
  }
  cluster_wait();
}

typedef CUresult (*EncodeFn)(CUtensorMap*, CUtensorMapDataType, cuuint32_t, void*, const cuuint64_t*, const cuuint64_t*,
                             const cuuint32_t*, const cuuint32_t*, CUtensorMapInterleave, CUtensorMapSwizzle,
                             CUtensorMapL2promotion, CUtensorMapFloatOOBfill);

void make_map(EncodeFn fn, CUtensorMap* m, const void* ptr, uint64_t rows, uint64_t cols, uint32_t box_rows) {
  cuuint64_t dims[2] = {cols, rows};
  cuuint64_t strides[1] = {cols * 2};
  cuuint32_t box[2] = {64, box_rows};
  cuuint32_t es[2] = {1, 1};
  fn(m, CU_TENSOR_MAP_DATA_TYPE_BFLOAT16, 2, const_cast<void*>(ptr), dims, strides, box, es, CU_TENSOR_MAP_INTERLEAVE_NONE,
     CU_TENSOR_MAP_SWIZZLE_128B, CU_TENSOR_MAP_L2_PROMOTION_L2_256B, CU_TENSOR_MAP_FLOAT_OOB_FILL_NONE);
}

void make_act_map(EncodeFn fn, CUtensorMap* m, const void* ptr, uint64_t cols) {
  cuuint64_t dims[3] = {cols, SEQ / 2, 2};
  cuuint64_t strides[2] = {cols * 4, cols * 2};
  cuuint32_t box[3] = {64, 64, 2};
  cuuint32_t es[3] = {1, 1, 1};
  fn(m, CU_TENSOR_MAP_DATA_TYPE_BFLOAT16, 3, const_cast<void*>(ptr), dims, strides, box, es, CU_TENSOR_MAP_INTERLEAVE_NONE,
     CU_TENSOR_MAP_SWIZZLE_128B, CU_TENSOR_MAP_L2_PROMOTION_L2_128B, CU_TENSOR_MAP_FLOAT_OOB_FILL_NONE);
}

}

extern "C" void kernel_launch(void* const* d_in, const int* in_sizes, int n_in, void* d_out, int out_size) {
  (void)in_sizes; (void)n_in; (void)out_size;
  EncodeFn fn = nullptr;
  cudaDriverEntryPointQueryResult qr;
  cudaGetDriverEntryPoint("cuTensorMapEncodeTiled", (void**)&fn, cudaEnableDefault, &qr);
  Params p;
  cudaGetSymbolAddress((void**)&p.s, g_s);
  p.t = make_tabs();
  make_act_map(fn, &p.x0, d_in[0], DM);
  make_act_map(fn, &p.x, p.s->x, DM);
  make_act_map(fn, &p.o, p.s->o, DM);
  make_act_map(fn, &p.h, p.s->h, FF);
  make_map(fn, &p.wqkv, d_in[1], DM, 3 * DM, 32);
  make_map(fn, &p.wo, d_in[2], DM, DM, 64);
  make_map(fn, &p.wg, d_in[4], DM, FF, 64);
  make_map(fn, &p.wu, d_in[5], DM, FF, 64);
  {
    cuuint64_t dims[5] = {DM, 2, 4, 4, FF / 32};
    cuuint64_t strides[4] = {DM * 2, DM * 16, DM * 4, DM * 64};
    cuuint32_t box[5] = {64, 2, 4, 4, 2};
    cuuint32_t es[5] = {1, 1, 1, 1, 1};
    fn(&p.wd, CU_TENSOR_MAP_DATA_TYPE_BFLOAT16, 5, d_in[6], dims, strides, box, es, CU_TENSOR_MAP_INTERLEAVE_NONE,
       CU_TENSOR_MAP_SWIZZLE_128B, CU_TENSOR_MAP_L2_PROMOTION_L2_256B, CU_TENSOR_MAP_FLOAT_OOB_FILL_NONE);
  }
  p.out = (__nv_bfloat16*)d_out;
  cudaFuncSetAttribute(fused_kernel<true>, cudaFuncAttributeMaxDynamicSharedMemorySize, SMEM_BYTES);
  cudaFuncSetAttribute(fused_kernel<false>, cudaFuncAttributeMaxDynamicSharedMemorySize, SMEM_BYTES);
  bool by_sm;
  {
    int dev = 0, sms = 0, nclusters = 0;
    cudaGetDevice(&dev);
    cudaDeviceGetAttribute(&sms, cudaDevAttrMultiProcessorCount, dev);
    cudaLaunchConfig_t cfg = {};
    cfg.gridDim = dim3(NCTA + NSPARE);
    cfg.blockDim = dim3(384);
    cfg.dynamicSmemBytes = SMEM_BYTES;
    cudaOccupancyMaxActiveClusters(&nclusters, fused_kernel<true>, &cfg);
    by_sm = sms == 132 && nclusters == 66;
  }
  if (by_sm) fused_kernel<true><<<NCTA + NSPARE, 384, SMEM_BYTES, cudaStreamPerThread>>>(p);
  else fused_kernel<false><<<NCTA + NSPARE, 384, SMEM_BYTES, cudaStreamPerThread>>>(p);
}
```

```cpp
#include <cuda_runtime.h>
#include <cuda_bf16.h>
#include <cuda.h>
#include <stdint.h>

namespace {

constexpr int SEQ = 2048, DM = 1024, FF = 3584;
constexpr int NCTA = 128;
constexpr uint32_t CAP = 196608;
constexpr uint32_t KV_OFF = 163840;
constexpr uint32_t KV_WG = 14848;
constexpr uint32_t KV_K = 9216, KV_R = 14336;
constexpr uint32_t STG_OFF = CAP;
constexpr uint32_t MISC_OFF = CAP + 32768;
constexpr uint32_t CSQ_OFF = MISC_OFF + 384;
constexpr uint32_t CSG_OFF = CSQ_OFF + 1536;
constexpr uint32_t SMEM_BYTES = CSG_OFF + 512 + 16;
constexpr int NSPARE = 4;

constexpr uint32_t B_EMPTY = 0, B_FULL = 64, B_DONE = 128  , B_HGO = 144  , B_HALO = 160  , B_CSQ = 176  ,
                   B_CS = 192, B_CSFREE = 200, B_XL = 216, B_BOX1 = 224, M_TAG = CSG_OFF + 512 - MISC_OFF,
                   B_SLAB = 256  , B_SFULL = 256, B_SEMPTY = 320;

enum { F_NONE = 0, F_O0, F_O1, F_X1, F_X1B, F_H0, F_H1, F_X0, F_X0B, F_COUNT };
constexpr int NCS = 3 * DM + 2 * FF;

struct Scratch {
  uint4 flags[16 * 8];
  uint32_t epoch[256];
  float2 stats[8 * SEQ];
  uint4 part[8 * NCS / 4];
  uint4 halo[4 * 16 * 8 * 2 * 5 * 32];
  __nv_bfloat16 x[SEQ * DM], o[SEQ * DM], h[SEQ * FF];
};
__device__ __align__(1024) Scratch g_s;

constexpr int NSEG = 23, NST = 168;
struct Tabs { uint32_t seg[2 * NSEG + 2], seq[9][8], ring[2 * NST + 2]; };
struct Params {
  Scratch* s;
  __nv_bfloat16* out;
  Tabs t;
  CUtensorMap x0, x, o, h, wqkv, wo, wg, wu, wd;
};

__device__ __forceinline__ uint32_t smem_u32(const void* p) { return (uint32_t)__cvta_generic_to_shared(p); }
__device__ __forceinline__ void mbar_init(uint32_t bar, uint32_t cnt) {
  asm volatile("mbarrier.init.shared::cta.b64 [%0], %1;" ::"r"(bar), "r"(cnt));
}
__device__ __forceinline__ void mbar_expect_tx(uint32_t bar, uint32_t bytes) {
  asm volatile("mbarrier.arrive.expect_tx.shared::cta.b64 _, [%0], %1;" ::"r"(bar), "r"(bytes) : "memory");
}
__device__ __forceinline__ void mbar_arrive(uint32_t bar) {
  asm volatile("mbarrier.arrive.shared::cta.b64 _, [%0];" ::"r"(bar) : "memory");
}
__device__ __forceinline__ bool mbar_try(uint32_t bar, uint32_t parity) {
  uint32_t ok;
  asm volatile("{\n.reg .pred p;\nmbarrier.try_wait.parity.shared::cta.b64 p, [%1], %2;\nselp.u32 %0, 1, 0, p;\n}"
               : "=r"(ok) : "r"(bar), "r"(parity) : "memory");
  return ok;
}
__device__ __forceinline__ void mbar_wait(uint32_t bar, uint32_t parity) {
  uint32_t n = 0;
  while (!mbar_try(bar, parity)) {
    if (++n > (1u << 20)) __trap();
  }
}
__device__ __forceinline__ void mbar_wait_idle(uint32_t bar, uint32_t parity) {
  uint32_t n = 0, ok;
  do {
    asm volatile("{\n.reg .pred p;\nmbarrier.try_wait.parity.shared::cta.b64 p, [%1], %2, %3;\nselp.u32 %0, 1, 0, p;\n}"
                 : "=r"(ok) : "r"(bar), "r"(parity), "n"(20000) : "memory");
    if (++n > (1u << 16)) __trap();
  } while (!ok);
}
__device__ __forceinline__ void tma_load(uint32_t dst, const void* tm, uint32_t bar, int c0, int c1) {
  asm volatile("cp.async.bulk.tensor.2d.shared::cluster.global.mbarrier::complete_tx::bytes [%0], [%1, {%3, %4}], [%2];"
               ::"r"(dst), "l"(tm), "r"(bar), "r"(c0), "r"(c1) : "memory");
}
__device__ __forceinline__ void tma_load3(uint32_t dst, const void* tm, uint32_t bar, int c0, int c1) {
  asm volatile("cp.async.bulk.tensor.3d.shared::cluster.global.mbarrier::complete_tx::bytes [%0], [%1, {%3, %4, %5}], [%2];"
               ::"r"(dst), "l"(tm), "r"(bar), "r"(c0), "r"(c1), "r"(0) : "memory");
}
__device__ __forceinline__ void tma_store3(const void* tm, uint32_t src, int c0, int c1) {
  asm volatile("cp.async.bulk.tensor.3d.global.shared::cta.bulk_group [%0, {%2, %3, %4}], [%1];\n"
               "cp.async.bulk.commit_group;\ncp.async.bulk.wait_group 0;" ::"l"(tm), "r"(src), "r"(c0), "r"(c1), "r"(0) : "memory");
}
__device__ __forceinline__ void tma_load_mc(uint32_t dst, const void* tm, uint32_t bar, int c0, int c1) {
  asm volatile("cp.async.bulk.tensor.2d.shared::cluster.global.mbarrier::complete_tx::bytes.multicast::cluster [%0], [%1, {%3, %4}], [%2], %5;"
               ::"r"(dst), "l"(tm), "r"(bar), "r"(c0), "r"(c1), "h"((uint16_t)3) : "memory");
}
__device__ __forceinline__ void tma_load5_mc(uint32_t dst, const void* tm, uint32_t bar, int c0, int c4) {
  asm volatile("cp.async.bulk.tensor.5d.shared::cluster.global.mbarrier::complete_tx::bytes.multicast::cluster [%0], [%1, {%3, %6, %6, %6, %4}], [%2], %5;"
               ::"r"(dst), "l"(tm), "r"(bar), "r"(c0), "r"(c4), "h"((uint16_t)3), "r"(0) : "memory");
}
__device__ __forceinline__ void fence_proxy_async() { asm volatile("fence.proxy.async.global;" ::: "memory"); }
__device__ __forceinline__ void st_tag(uint4* p, uint32_t a, uint32_t b, uint32_t c, uint32_t tag) {
  asm volatile("{\n.reg .b128 t;\n.reg .b64 lo, hi;\nmov.b64 lo, {%1, %2};\nmov.b64 hi, {%3, %4};\nmov.b128 t, {lo, hi};\n"
               "st.relaxed.gpu.global.b128 [%0], t;\n}" ::"l"(p), "r"(a), "r"(b), "r"(c), "r"(tag) : "memory");
}
__device__ __forceinline__ void st_tag_if(bool on, uint4* p, uint32_t a, uint32_t b, uint32_t c, uint32_t tag) {
  asm volatile("{\n.reg .b128 t;\n.reg .b64 lo, hi;\n.reg .pred p;\nsetp.ne.u32 p, %5, 0;\nmov.b64 lo, {%1, %2};\nmov.b64 hi, {%3, %4};\nmov.b128 t, {lo, hi};\n"
               "@p st.relaxed.gpu.global.b128 [%0], t;\n}" ::"l"(p), "r"(a), "r"(b), "r"(c), "r"(tag), "r"((uint32_t)on) : "memory");
}
__device__ __forceinline__ uint4 ld_tag(const uint4* p) {
  uint4 v;
  asm volatile("{\n.reg .b128 t;\n.reg .b64 lo, hi;\nld.relaxed.gpu.global.b128 t, [%4];\nmov.b128 {lo, hi}, t;\n"
               "mov.b64 {%0, %1}, lo;\nmov.b64 {%2, %3}, hi;\n}" : "=r"(v.x), "=r"(v.y), "=r"(v.z), "=r"(v.w) : "l"(p) : "memory");
  return v;
}
__device__ __forceinline__ float tanh_approx(float x) { float y; asm("tanh.approx.f32 %0, %1;" : "=f"(y) : "f"(x)); return y; }
__device__ __forceinline__ void fence_proxy_async_smem() { asm volatile("fence.proxy.async.shared::cta;" ::: "memory"); }
__device__ __forceinline__ void fence_gpu() { asm volatile("fence.release.gpu;" ::: "memory"); }
__device__ __forceinline__ uint32_t ld_epoch(const Params& p) {
  uint32_t e;
  asm volatile("ld.relaxed.gpu.global.u32 %0, [%1];" : "=r"(e) : "l"(p.s->epoch + blockIdx.x) : "memory");
  return e;
}
__device__ __forceinline__ void st_flags(void* p, uint32_t v) {
  asm volatile("st.relaxed.gpu.global.u16 [%0], %1;" ::"l"(p), "h"((uint16_t)((v & 255) * 257)) : "memory");
}
__device__ __forceinline__ uint32_t ld_flag(const void* p) {
  uint32_t v;
  asm volatile("ld.relaxed.gpu.global.u8 %0, [%1];" : "=r"(v) : "l"(p) : "memory");
  return v;
}
__device__ __forceinline__ void wgmma_fence() { asm volatile("wgmma.fence.sync.aligned;" ::: "memory"); }
__device__ __forceinline__ void wgmma_commit() { asm volatile("wgmma.commit_group.sync.aligned;" ::: "memory"); }
template <int N> __device__ __forceinline__ void wgmma_wait() {
  asm volatile("wgmma.wait_group.sync.aligned %0;" ::"n"(N) : "memory");
}
__device__ __forceinline__ void cluster_arrive() { asm volatile("barrier.cluster.arrive.relaxed;" ::: "memory"); }
__device__ __forceinline__ void cluster_wait() { asm volatile("barrier.cluster.wait;" ::: "memory"); }
__device__ __forceinline__ void bar_sync(int id, int n) { asm volatile("bar.sync %0, %1;" ::"r"(id), "r"(n) : "memory"); }
__device__ __forceinline__ uint32_t pack_bf16(float lo, float hi) {
  uint32_t r;
  asm("cvt.rn.bf16x2.f32 %0, %1, %2;" : "=r"(r) : "f"(hi), "f"(lo));
  return r;
}
__device__ __forceinline__ float bf_lo(uint32_t v) { return __uint_as_float(v << 16); }
__device__ __forceinline__ float bf_hi(uint32_t v) { return __uint_as_float(v & 0xffff0000u); }
__device__ __forceinline__ void stsm4(uint32_t a, uint32_t r0, uint32_t r1, uint32_t r2, uint32_t r3) {
  asm volatile("stmatrix.sync.aligned.m8n8.x4.shared.b16 [%0], {%1, %2, %3, %4};" ::"r"(a), "r"(r0), "r"(r1), "r"(r2), "r"(r3) : "memory");
}
__device__ __forceinline__ void ldsm4(uint32_t a, uint32_t& r0, uint32_t& r1, uint32_t& r2, uint32_t& r3) {
  asm volatile("ldmatrix.sync.aligned.m8n8.x4.shared.b16 {%0, %1, %2, %3}, [%4];" : "=r"(r0), "=r"(r1), "=r"(r2), "=r"(r3) : "r"(a) : "memory");
}
__device__ __forceinline__ void ldsm4t(uint32_t a, uint32_t& r0, uint32_t& r1, uint32_t& r2, uint32_t& r3) {
  asm volatile("ldmatrix.sync.aligned.m8n8.x4.trans.shared.b16 {%0, %1, %2, %3}, [%4];" : "=r"(r0), "=r"(r1), "=r"(r2), "=r"(r3) : "r"(a) : "memory");
}
__device__ __forceinline__ void mma16816(float (&c)[4], uint32_t a0, uint32_t a1, uint32_t a2, uint32_t a3, uint32_t b0, uint32_t b1) {
  asm volatile("mma.sync.aligned.m16n8k16.row.col.f32.bf16.bf16.f32 {%0,%1,%2,%3}, {%4,%5,%6,%7}, {%8,%9}, {%0,%1,%2,%3};"
               : "+f"(c[0]), "+f"(c[1]), "+f"(c[2]), "+f"(c[3]) : "r"(a0), "r"(a1), "r"(a2), "r"(a3), "r"(b0), "r"(b1));
}
__device__ __forceinline__ float ex2(float x) { float y; asm("ex2.approx.ftz.f32 %0, %1;" : "=f"(y) : "f"(x)); return y; }
__device__ __forceinline__ float rcp(float x) { float y; asm("rcp.approx.ftz.f32 %0, %1;" : "=f"(y) : "f"(x)); return y; }
__device__ __forceinline__ uint32_t pin(uint32_t a) {
  uint32_t r;
  asm volatile("mov.u32 %0, %1;" : "=r"(r) : "r"(a) : "memory");
  return r;
}
__device__ __forceinline__ float lds32f(uint32_t a) {
  float v;
  asm volatile("ld.shared.f32 %0, [%1];" : "=f"(v) : "r"(a) : "memory");
  return v;
}
__device__ __forceinline__ void sts32f(uint32_t a, float v) { asm volatile("st.shared.f32 [%0], %1;" ::"r"(a), "f"(v) : "memory"); }
__device__ __forceinline__ void sts64f(uint32_t a, float x, float y) { asm volatile("st.shared.v2.f32 [%0], {%1, %2};" ::"r"(a), "f"(x), "f"(y) : "memory"); }
__device__ __forceinline__ float2 ld_b64(const void* p) {
  float2 v;
  asm volatile("{\n.reg .b64 t;\nld.relaxed.gpu.global.b64 t, [%2];\nmov.b64 {%0, %1}, t;\n}" : "=f"(v.x), "=f"(v.y) : "l"(p) : "memory");
  return v;
}
__device__ __forceinline__ void st_b64(void* p, uint32_t x, uint32_t y) {
  asm volatile("{\n.reg .b64 t;\nmov.b64 t, {%1, %2};\nst.relaxed.gpu.global.b64 [%0], t;\n}" ::"l"(p), "r"(x), "r"(y) : "memory");
}
__device__ __forceinline__ uint4 lds128(uint32_t a) {
  uint4 v;
  asm volatile("ld.shared.v4.u32 {%0, %1, %2, %3}, [%4];" : "=r"(v.x), "=r"(v.y), "=r"(v.z), "=r"(v.w) : "r"(a) : "memory");
  return v;
}
__device__ __forceinline__ float qsum(float v) {
  v += __shfl_xor_sync(0xffffffffu, v, 1);
  v += __shfl_xor_sync(0xffffffffu, v, 2);
  return v;
}
__device__ __forceinline__ void sts128(uint32_t a, uint32_t x, uint32_t y, uint32_t z, uint32_t w) {
  asm volatile("st.shared.v4.u32 [%0], {%1, %2, %3, %4};" ::"r"(a), "r"(x), "r"(y), "r"(z), "r"(w) : "memory");
}
__device__ __forceinline__ float4 lds128f(uint32_t a) {
  float4 v;
  asm volatile("ld.shared.v4.f32 {%0, %1, %2, %3}, [%4];" : "=f"(v.x), "=f"(v.y), "=f"(v.z), "=f"(v.w) : "r"(a) : "memory");
  return v;
}
__device__ __forceinline__ void stg128(void* p, uint32_t x, uint32_t y, uint32_t z, uint32_t w) {
  asm volatile("st.global.v4.u32 [%0], {%1, %2, %3, %4};" ::"l"(p), "r"(x), "r"(y), "r"(z), "r"(w) : "memory");
}
__device__ __forceinline__ void mma1688z(float (&c)[4], uint32_t a0, uint32_t b0) {
  asm volatile("mma.sync.aligned.m16n8k8.row.col.f32.bf16.bf16.f32 {%0,%1,%2,%3}, {%4,%5}, {%6}, {%7,%7,%7,%7};"
               : "=f"(c[0]), "=f"(c[1]), "=f"(c[2]), "=f"(c[3]) : "r"(a0), "r"(0u), "r"(b0), "f"(0.f));
}
__device__ __forceinline__ void mma16816z(float (&c)[4], uint32_t a0, uint32_t a1, uint32_t a2, uint32_t a3, uint32_t b0, uint32_t b1) {
  asm volatile("mma.sync.aligned.m16n8k16.row.col.f32.bf16.bf16.f32 {%0,%1,%2,%3}, {%4,%5,%6,%7}, {%8,%9}, {%10,%10,%10,%10};"
               : "=f"(c[0]), "=f"(c[1]), "=f"(c[2]), "=f"(c[3]) : "r"(a0), "r"(a1), "r"(a2), "r"(a3), "r"(b0), "r"(b1), "f"(0.f));
}

__device__ __forceinline__ void wgmma_n128(float (&d0)[64], uint64_t da, uint64_t db) {
  asm volatile(
    "wgmma.mma_async.sync.aligned.m64n128k16.f32.bf16.bf16 "
    "{%0,%1,%2,%3,%4,%5,%6,%7,%8,%9,%10,%11,%12,%13,%14,%15,"
    "%16,%17,%18,%19,%20,%21,%22,%23,%24,%25,%26,%27,%28,%29,%30,%31,"
    "%32,%33,%34,%35,%36,%37,%38,%39,%40,%41,%42,%43,%44,%45,%46,%47,"
    "%48,%49,%50,%51,%52,%53,%54,%55,%56,%57,%58,%59,%60,%61,%62,%63},"
    " %64, %65, 1, 1, 1, 0, 1;"
    : "+f"(d0[0]), "+f"(d0[1]), "+f"(d0[2]), "+f"(d0[3]), "+f"(d0[4]), "+f"(d0[5]), "+f"(d0[6]), "+f"(d0[7]),
      "+f"(d0[8]), "+f"(d0[9]), "+f"(d0[10]), "+f"(d0[11]), "+f"(d0[12]), "+f"(d0[13]), "+f"(d0[14]), "+f"(d0[15]),
      "+f"(d0[16]), "+f"(d0[17]), "+f"(d0[18]), "+f"(d0[19]), "+f"(d0[20]), "+f"(d0[21]), "+f"(d0[22]), "+f"(d0[23]),
      "+f"(d0[24]), "+f"(d0[25]), "+f"(d0[26]), "+f"(d0[27]), "+f"(d0[28]), "+f"(d0[29]), "+f"(d0[30]), "+f"(d0[31]),
      "+f"(d0[32]), "+f"(d0[33]), "+f"(d0[34]), "+f"(d0[35]), "+f"(d0[36]), "+f"(d0[37]), "+f"(d0[38]), "+f"(d0[39]),
      "+f"(d0[40]), "+f"(d0[41]), "+f"(d0[42]), "+f"(d0[43]), "+f"(d0[44]), "+f"(d0[45]), "+f"(d0[46]), "+f"(d0[47]),
      "+f"(d0[48]), "+f"(d0[49]), "+f"(d0[50]), "+f"(d0[51]), "+f"(d0[52]), "+f"(d0[53]), "+f"(d0[54]), "+f"(d0[55]),
      "+f"(d0[56]), "+f"(d0[57]), "+f"(d0[58]), "+f"(d0[59]), "+f"(d0[60]), "+f"(d0[61]), "+f"(d0[62]), "+f"(d0[63])
    : "l"(da), "l"(db));
}
__device__ __forceinline__ void wgmma_n128_init(float (&d0)[64], uint64_t da, uint64_t db) {
  asm volatile(
    "wgmma.mma_async.sync.aligned.m64n128k16.f32.bf16.bf16 "
    "{%0,%1,%2,%3,%4,%5,%6,%7,%8,%9,%10,%11,%12,%13,%14,%15,"
    "%16,%17,%18,%19,%20,%21,%22,%23,%24,%25,%26,%27,%28,%29,%30,%31,"
    "%32,%33,%34,%35,%36,%37,%38,%39,%40,%41,%42,%43,%44,%45,%46,%47,"
    "%48,%49,%50,%51,%52,%53,%54,%55,%56,%57,%58,%59,%60,%61,%62,%63},"
    " %64, %65, 0, 1, 1, 0, 1;"
    : "=f"(d0[0]), "=f"(d0[1]), "=f"(d0[2]), "=f"(d0[3]), "=f"(d0[4]), "=f"(d0[5]), "=f"(d0[6]), "=f"(d0[7]),
      "=f"(d0[8]), "=f"(d0[9]), "=f"(d0[10]), "=f"(d0[11]), "=f"(d0[12]), "=f"(d0[13]), "=f"(d0[14]), "=f"(d0[15]),
      "=f"(d0[16]), "=f"(d0[17]), "=f"(d0[18]), "=f"(d0[19]), "=f"(d0[20]), "=f"(d0[21]), "=f"(d0[22]), "=f"(d0[23]),
      "=f"(d0[24]), "=f"(d0[25]), "=f"(d0[26]), "=f"(d0[27]), "=f"(d0[28]), "=f"(d0[29]), "=f"(d0[30]), "=f"(d0[31]),
      "=f"(d0[32]), "=f"(d0[33]), "=f"(d0[34]), "=f"(d0[35]), "=f"(d0[36]), "=f"(d0[37]), "=f"(d0[38]), "=f"(d0[39]),
      "=f"(d0[40]), "=f"(d0[41]), "=f"(d0[42]), "=f"(d0[43]), "=f"(d0[44]), "=f"(d0[45]), "=f"(d0[46]), "=f"(d0[47]),
      "=f"(d0[48]), "=f"(d0[49]), "=f"(d0[50]), "=f"(d0[51]), "=f"(d0[52]), "=f"(d0[53]), "=f"(d0[54]), "=f"(d0[55]),
      "=f"(d0[56]), "=f"(d0[57]), "=f"(d0[58]), "=f"(d0[59]), "=f"(d0[60]), "=f"(d0[61]), "=f"(d0[62]), "=f"(d0[63])
    : "l"(da), "l"(db));
}
__device__ __forceinline__ void wgmma_n192(float (&d0)[96], uint64_t da, uint64_t db) {
  asm volatile(
    "wgmma.mma_async.sync.aligned.m64n192k16.f32.bf16.bf16 "
    "{%0,%1,%2,%3,%4,%5,%6,%7,%8,%9,%10,%11,%12,%13,%14,%15,"
    "%16,%17,%18,%19,%20,%21,%22,%23,%24,%25,%26,%27,%28,%29,%30,%31,"
    "%32,%33,%34,%35,%36,%37,%38,%39,%40,%41,%42,%43,%44,%45,%46,%47,"
    "%48,%49,%50,%51,%52,%53,%54,%55,%56,%57,%58,%59,%60,%61,%62,%63,"
    "%64,%65,%66,%67,%68,%69,%70,%71,%72,%73,%74,%75,%76,%77,%78,%79,"
    "%80,%81,%82,%83,%84,%85,%86,%87,%88,%89,%90,%91,%92,%93,%94,%95},"
    " %96, %97, 1, 1, 1, 0, 1;"
    : "+f"(d0[0]), "+f"(d0[1]), "+f"(d0[2]), "+f"(d0[3]), "+f"(d0[4]), "+f"(d0[5]), "+f"(d0[6]), "+f"(d0[7]),
      "+f"(d0[8]), "+f"(d0[9]), "+f"(d0[10]), "+f"(d0[11]), "+f"(d0[12]), "+f"(d0[13]), "+f"(d0[14]), "+f"(d0[15]),
      "+f"(d0[16]), "+f"(d0[17]), "+f"(d0[18]), "+f"(d0[19]), "+f"(d0[20]), "+f"(d0[21]), "+f"(d0[22]), "+f"(d0[23]),
      "+f"(d0[24]), "+f"(d0[25]), "+f"(d0[26]), "+f"(d0[27]), "+f"(d0[28]), "+f"(d0[29]), "+f"(d0[30]), "+f"(d0[31]),
      "+f"(d0[32]), "+f"(d0[33]), "+f"(d0[34]), "+f"(d0[35]), "+f"(d0[36]), "+f"(d0[37]), "+f"(d0[38]), "+f"(d0[39]),
      "+f"(d0[40]), "+f"(d0[41]), "+f"(d0[42]), "+f"(d0[43]), "+f"(d0[44]), "+f"(d0[45]), "+f"(d0[46]), "+f"(d0[47]),
      "+f"(d0[48]), "+f"(d0[49]), "+f"(d0[50]), "+f"(d0[51]), "+f"(d0[52]), "+f"(d0[53]), "+f"(d0[54]), "+f"(d0[55]),
      "+f"(d0[56]), "+f"(d0[57]), "+f"(d0[58]), "+f"(d0[59]), "+f"(d0[60]), "+f"(d0[61]), "+f"(d0[62]), "+f"(d0[63]),
      "+f"(d0[64]), "+f"(d0[65]), "+f"(d0[66]), "+f"(d0[67]), "+f"(d0[68]), "+f"(d0[69]), "+f"(d0[70]), "+f"(d0[71]),
      "+f"(d0[72]), "+f"(d0[73]), "+f"(d0[74]), "+f"(d0[75]), "+f"(d0[76]), "+f"(d0[77]), "+f"(d0[78]), "+f"(d0[79]),
      "+f"(d0[80]), "+f"(d0[81]), "+f"(d0[82]), "+f"(d0[83]), "+f"(d0[84]), "+f"(d0[85]), "+f"(d0[86]), "+f"(d0[87]),
      "+f"(d0[88]), "+f"(d0[89]), "+f"(d0[90]), "+f"(d0[91]), "+f"(d0[92]), "+f"(d0[93]), "+f"(d0[94]), "+f"(d0[95])
    : "l"(da), "l"(db));
}
__device__ __forceinline__ void wgmma_n192_init(float (&d0)[96], uint64_t da, uint64_t db) {
  asm volatile(
    "wgmma.mma_async.sync.aligned.m64n192k16.f32.bf16.bf16 "
    "{%0,%1,%2,%3,%4,%5,%6,%7,%8,%9,%10,%11,%12,%13,%14,%15,"
    "%16,%17,%18,%19,%20,%21,%22,%23,%24,%25,%26,%27,%28,%29,%30,%31,"
    "%32,%33,%34,%35,%36,%37,%38,%39,%40,%41,%42,%43,%44,%45,%46,%47,"
    "%48,%49,%50,%51,%52,%53,%54,%55,%56,%57,%58,%59,%60,%61,%62,%63,"
    "%64,%65,%66,%67,%68,%69,%70,%71,%72,%73,%74,%75,%76,%77,%78,%79,"
    "%80,%81,%82,%83,%84,%85,%86,%87,%88,%89,%90,%91,%92,%93,%94,%95},"
    " %96, %97, 0, 1, 1, 0, 1;"
    : "=f"(d0[0]), "=f"(d0[1]), "=f"(d0[2]), "=f"(d0[3]), "=f"(d0[4]), "=f"(d0[5]), "=f"(d0[6]), "=f"(d0[7]),
      "=f"(d0[8]), "=f"(d0[9]), "=f"(d0[10]), "=f"(d0[11]), "=f"(d0[12]), "=f"(d0[13]), "=f"(d0[14]), "=f"(d0[15]),
      "=f"(d0[16]), "=f"(d0[17]), "=f"(d0[18]), "=f"(d0[19]), "=f"(d0[20]), "=f"(d0[21]), "=f"(d0[22]), "=f"(d0[23]),
      "=f"(d0[24]), "=f"(d0[25]), "=f"(d0[26]), "=f"(d0[27]), "=f"(d0[28]), "=f"(d0[29]), "=f"(d0[30]), "=f"(d0[31]),
      "=f"(d0[32]), "=f"(d0[33]), "=f"(d0[34]), "=f"(d0[35]), "=f"(d0[36]), "=f"(d0[37]), "=f"(d0[38]), "=f"(d0[39]),
      "=f"(d0[40]), "=f"(d0[41]), "=f"(d0[42]), "=f"(d0[43]), "=f"(d0[44]), "=f"(d0[45]), "=f"(d0[46]), "=f"(d0[47]),
      "=f"(d0[48]), "=f"(d0[49]), "=f"(d0[50]), "=f"(d0[51]), "=f"(d0[52]), "=f"(d0[53]), "=f"(d0[54]), "=f"(d0[55]),
      "=f"(d0[56]), "=f"(d0[57]), "=f"(d0[58]), "=f"(d0[59]), "=f"(d0[60]), "=f"(d0[61]), "=f"(d0[62]), "=f"(d0[63]),
      "=f"(d0[64]), "=f"(d0[65]), "=f"(d0[66]), "=f"(d0[67]), "=f"(d0[68]), "=f"(d0[69]), "=f"(d0[70]), "=f"(d0[71]),
      "=f"(d0[72]), "=f"(d0[73]), "=f"(d0[74]), "=f"(d0[75]), "=f"(d0[76]), "=f"(d0[77]), "=f"(d0[78]), "=f"(d0[79]),
      "=f"(d0[80]), "=f"(d0[81]), "=f"(d0[82]), "=f"(d0[83]), "=f"(d0[84]), "=f"(d0[85]), "=f"(d0[86]), "=f"(d0[87]),
      "=f"(d0[88]), "=f"(d0[89]), "=f"(d0[90]), "=f"(d0[91]), "=f"(d0[92]), "=f"(d0[93]), "=f"(d0[94]), "=f"(d0[95])
    : "l"(da), "l"(db));
}
enum { A_LOC = 0, A_X = 1, A_O = 2, A_H = 3 };
enum { W_QKV = 0, W_O = 1, W_G = 2, W_D = 3 };
enum { K_L = 0, K_E7 = 1, K_O7 = 2, K_OL = 3, K_OR = 4, K_LIN = 5 };
struct Seg { int nb, n, a, w, c0, c1, ks, dep; };
constexpr int NOA = 2;
constexpr Seg SEGS[NSEG] = {
  {3, 2, A_LOC, W_QKV, 1, 0, K_L, F_NONE},
  {3, 2, A_LOC, W_QKV, 0, 0, K_L, F_NONE},
  {3, 7, A_X, W_QKV, 0, 0, K_E7, F_X0},
  {3, 7, A_X, W_QKV, 0, 0, K_O7, F_X0B},
  {3, 7, A_X, W_QKV, 1, 0, K_E7, F_NONE},
  {3, 7, A_X, W_QKV, 1, 0, K_O7, F_NONE},
  {2, 8, A_O, W_O, 0, 0, K_LIN, F_O0},
  {2, 1, A_LOC, W_O, 0, 0, K_OL, F_NONE},
  {2, 7, A_O, W_O, 0, 0, K_OR, F_O1},
  {2, 2, A_LOC, W_G, 2, 0, K_L, F_NONE},
  {4, 2, A_LOC, W_G, 0, 1, K_L, F_NONE},
  {4, 7, A_X, W_G, 0, 1, K_E7, F_X1},
  {2, 7, A_X, W_G, 0, 0, K_O7, F_X1B},
  {4, 7, A_X, W_G, 2, 1, K_O7, F_NONE},
  {4, 7, A_X, W_G, 2, 3, K_E7, F_NONE},
  {4, 2, A_LOC, W_G, 4, 3, K_L, F_NONE},
  {4, 7, A_X, W_G, 4, 3, K_O7, F_NONE},
  {4, 7, A_X, W_G, 4, 5, K_E7, F_NONE},
  {4, 2, A_LOC, W_G, 6, 5, K_L, F_NONE},
  {4, 7, A_X, W_G, 6, 5, K_O7, F_NONE},
  {2, 7, A_X, W_G, 6, 0, K_E7, F_NONE},
  {2, 32, A_H, W_D, 0, 0, K_LIN, F_H0},
  {2, 24, A_H, W_D, 4, 0, K_LIN, F_H1},
};
constexpr Tabs make_tabs() {
  Tabs t{};
  int pa[2 * NST] = {}, pb[2 * NST] = {}, sa[2 * NST] = {}, sb[2 * NST] = {};
  int pos = 12, it = 0;
  constexpr int o0 = 32;
  for (int sg = 0; sg < 2 * NSEG; sg++) {
    Seg g = SEGS[sg % NSEG];
    if (sg < 6) { g.a = A_X; g.dep = F_NONE; }
    for (int k = 0; k < g.n; k++, it++) {
      const int cap = it % NST < o0 + 3 ? 20 : 24;
      const int a = (g.a == A_LOC && g.n > 1 && g.c0 < 4) ? 0 : 2, b = g.nb, rem = cap - pos;
      sa[it] = g.a == A_LOC ? 0 : 2; sb[it] = b;
      if (rem >= a + b) { pa[it] = pos; pb[it] = pos + a; pos += a + b; }
      else if (a && rem == a) { pa[it] = pos; pb[it] = 0; pos = b; }
      else if (a && rem == b) { pb[it] = pos; pa[it] = 0; pos = a; }
      else { pa[it] = 0; pb[it] = a; pos = a + b; }
      if (g.a == A_LOC) pa[it] = 24 + 2 * k;
    }
    t.seg[sg] = (uint32_t)(g.n | g.nb << 6 | g.a << 9 | g.w << 11 | g.c0 << 13 | g.c1 << 16 | g.ks << 19 | g.dep << 22);
  }
  for (int i = 0; i < 2 * NST; i++) {
    int lag[2] = {8, 8};
    const int p[2] = {pa[i], pb[i]}, n[2] = {sa[i], sb[i]}, io = i % NST - o0;
    for (int x = 0; x < 2; x++) {
      for (int l = i < 8 ? i : 8; l >= 1; l--) {
        const int q[2] = {pa[i - l], pb[i - l]}, m[2] = {sa[i - l], sb[i - l]};
        for (int y = 0; y < 2; y++)
          if (n[x] && m[y] && p[x] < q[y] + m[y] && q[y] < p[x] + n[x]) lag[x] = l;
      }
      if (io > 0 && io < 8 && p[x] >= 20 && io - NOA < lag[x]) lag[x] = io - NOA;
    }
    if (i == NST + 3) lag[1] = 6;
    if (i < o0 && lag[0] < lag[1]) lag[1] = lag[0];
    t.ring[i] = (uint32_t)(pa[i] * 512 | lag[1] | lag[0] << 4 | pb[i] * 512 << 16);
  }
  int waits[2 * NST] = {};
  for (int i = 0; i < 2 * NST; i++)
    for (int x = 0; x < 2; x++) {
      const int j = i - (int)((t.ring[i] >> (4 * x)) & 15);
      if (j >= 0 && (!x || (i >= o0 && sa[i]))) waits[j]++;
    }
  for (int j = 0; j < 2 * NST - 8; j++)
    for (int x = 1; x >= 0; x--)
      for (int i = j + 7; i > j && !waits[j]; i--) {
        const int q = i - (int)((t.ring[i] >> (4 * x)) & 15);
        if (q < j && waits[q] > 1 && (!x || sa[i])) { waits[q]--; waits[j]++; t.ring[i] -= (uint32_t)(j - q) << (4 * x); }
      }
  for (int jc = 0; jc < 8; jc++)
    for (int ks = 0; ks < K_LIN; ks++)
      for (int i = 0; i < 8; i++) {
        const int u = i == jc ? 7 : i;
        t.seq[jc][ks] |= (uint32_t)(ks == K_L ? jc * 2 + (i & 1) : ks == K_OL ? 8 + jc : ks == K_OR ? 8 + u : u * 2 + (ks != K_E7)) << (4 * i);
      }
  t.seq[8][K_L] = 0x10; t.seq[8][K_E7] = 0x8765432; t.seq[8][K_O7] = 0xfedcba9;
  return t;
}

constexpr uint32_t RING0 = make_tabs().ring[0];

__device__ __forceinline__ bool elect_one() {
  uint32_t pred;
  asm volatile("{\n.reg .pred p;\nelect.sync _|p, 0xffffffff;\nselp.u32 %0, 1, 0, p;\n}" : "=r"(pred));
  return pred;
}

struct Ctx {
  const Params& p;
  uint32_t sb;
  uint32_t it;
  uint32_t lp;
  uint32_t ebar;
  bool rel;
  uint32_t da, db;
  int w, wg, wi, lane;
  int rb, jc;
  float m0, r0, m1, r1;
};
struct Stage { uint64_t da, db; };
struct Stats { float2 a, b, c, d; };

__device__ __forceinline__ uint32_t ld_tag_s(uint32_t sb) { return __float_as_uint(lds32f(sb + MISC_OFF + M_TAG)); }
__device__ __forceinline__ void carrive(const Ctx& c, uint32_t bar) {
  __syncwarp();
  if (c.lane == 0) mbar_arrive(c.sb + MISC_OFF + bar);
}

__device__ __forceinline__ Stage peek(const Ctx& c) {
  const uint32_t e = c.p.t.ring[c.it];
  Stage s;
  asm("mov.b64 %0, {%1, 0x40000040};" : "=l"(s.da) : "r"(c.da + (e & 0x3e00)));
  asm("mov.b64 %0, {%1, 0x40000040};" : "=l"(s.db) : "r"(c.db + (e >> 16)));
  return s;
}
__device__ __forceinline__ void wait_full(Ctx& c) {
  mbar_wait(c.sb + MISC_OFF + B_FULL + (c.it & 7) * 8, (c.it >> 3) & 1);
  c.it++;
}
__device__ __forceinline__ void release(Ctx& c) {
  if (c.rel) asm volatile("mbarrier.arrive.shared::cluster.b64 _, [%0];" ::"r"(c.ebar) : "memory");
  c.ebar = (c.ebar + 8) & ~64u;
}
__device__ __forceinline__ void load_stats(const Ctx& c, Stats& s) {
  const int lane = pin(c.lane);
  const float2* sp = c.p.s->stats + (lane & 3) * 2 * SEQ + pin(c.rb) * 128 + pin(c.w) * 16 + (lane >> 2);
  s.a = ld_b64(sp); s.b = ld_b64(sp + SEQ); s.c = ld_b64(sp + 8); s.d = ld_b64(sp + SEQ + 8);
}
__device__ __forceinline__ void combine2(float2 a, float2 b, float& mean, float& rstd) {
  mean = qsum(a.x + b.x) * 0.125f;
  const float d0 = a.x - mean, d1 = b.x - mean;
  const float m2 = qsum(a.y + b.y + 128.f * (d0 * d0 + d1 * d1));
  rstd = rsqrtf(m2 * (1.f / 1024.f) + 1e-5f);
}
__device__ __forceinline__ void combine_stats(Ctx& c, Stats& s, uint32_t tag) {
  uint32_t n = 0;
  while (true) {
    const uint32_t x = tag & 1, y = tag >> 1;
    const uint32_t bad = (__float_as_uint(s.a.x) ^ x) | (__float_as_uint(s.b.x) ^ x) | (__float_as_uint(s.c.x) ^ x) | (__float_as_uint(s.d.x) ^ x) |
                         (__float_as_uint(s.a.y) ^ y) | (__float_as_uint(s.b.y) ^ y) | (__float_as_uint(s.c.y) ^ y) | (__float_as_uint(s.d.y) ^ y);
    if (__all_sync(0xffffffffu, !(bad & 1))) break;
    if (++n > (1u << 18)) __trap();
    load_stats(c, s);
  }
  combine2(s.a, s.b, c.m0, c.r0);
  combine2(s.c, s.d, c.m1, c.r1);
}

template <bool INIT> __device__ __forceinline__ void mm(float (&A)[64], uint64_t da, uint64_t db) {
  if (INIT) wgmma_n128_init(A, da, db); else wgmma_n128(A, da, db);
}
template <bool INIT> __device__ __forceinline__ void mm(float (&A)[96], uint64_t da, uint64_t db) {
  if (INIT) wgmma_n192_init(A, da, db); else wgmma_n192(A, da, db);
}
__device__ __forceinline__ void keep(float& v) { asm volatile("" : "+f"(v)); }
__device__ __forceinline__ void keep(uint32_t& v) { asm volatile("" : "+r"(v)); }
template <int N> __device__ __forceinline__ void keep_all(float (&A)[N]) {
#pragma unroll
  for (int i = 0; i < N; i++) keep(A[i]);
}
__device__ __forceinline__ void cut(const Stage& s) {
  asm volatile("{\n.reg .pred p;\nsetp.eq.u32 p, %0, 0xffffffff;\n@p trap;\n}" ::"r"((uint32_t)s.db) : "memory");
}
struct Nop { __device__ __forceinline__ void operator()() const {} };
template <bool INIT, bool FIRST, int WAIT = 1, int N, class HOOK>
__device__ __forceinline__ void step1(Ctx& c, Stage& s, float (&A)[N], HOOK&& hook) {
  wait_full(c);
  wgmma_fence();
  mm<INIT>(A, s.da, s.db);
  if (!FIRST) {
    wgmma_commit();
    wgmma_wait<1>();
    release(c);
  }
  mm<false>(A, s.da + 2, s.db + 128);
  mm<false>(A, s.da + 4, s.db + 256);
  wgmma_commit();
  mm<false>(A, s.da + 6, s.db + 384);
  wgmma_commit();
  s = peek(c);
  if (sizeof(hook) > 1) cut(s);
  hook();
  if (WAIT == 2 || (WAIT == 1 && sizeof(hook) == 1)) wgmma_wait<1>();
}
template <bool INIT, int WAIT = 1, class HOOK>
__device__ __forceinline__ void step2(Ctx& c, Stage& s, float (&A)[64], float (&B)[64], HOOK&& hook) {
  wait_full(c);
  wgmma_fence();
  mm<INIT>(A, s.da, s.db);
  mm<INIT>(B, s.da, s.db + 1024);
  wgmma_commit();
  wgmma_wait<1>();
  release(c);
  mm<false>(A, s.da + 2, s.db + 128);
  mm<false>(B, s.da + 2, s.db + 1152);
  mm<false>(A, s.da + 4, s.db + 256);
  mm<false>(B, s.da + 4, s.db + 1280);
  wgmma_commit();
  mm<false>(A, s.da + 6, s.db + 384);
  mm<false>(B, s.da + 6, s.db + 1408);
  wgmma_commit();
  s = peek(c);
  if (sizeof(hook) > 1) cut(s);
  hook();
  if (WAIT == 2 || (WAIT == 1 && sizeof(hook) == 1)) wgmma_wait<1>();
}
template <bool INIT>
__device__ __forceinline__ void stage128(float (&A)[64], uint64_t da, uint64_t db) {
  mm<INIT>(A, da, db);
  mm<false>(A, da + 2, db + 128);
  mm<false>(A, da + 4, db + 256);
  mm<false>(A, da + 6, db + 384);
}

__device__ __forceinline__ uint32_t warp_rows(const Ctx& c) { return c.sb + STG_OFF + pin(c.w) * 2048; }
__device__ __forceinline__ uint32_t stg_base(uint32_t rows, int lane) {
  return rows + (lane & 15) * 128 + (((lane >> 4) ^ (lane & 7)) << 4);
}
__device__ __forceinline__ int seq_row(const Ctx& c, int r) {
  const int w = pin(c.w);
  return pin(c.rb) * 128 + (w & 3) * 32 + (w >> 2) + 2 * r;
}
template <int H>
__device__ __forceinline__ void resid_init(const Ctx& c, float (&A)[64]) {
  const uint32_t sta = stg_base(warp_rows(c), pin(c.lane)) + H * 16384;
#pragma unroll
  for (int b = 0; b < 8; b += 2) {
    uint32_t v0, v1, v2, v3;
    ldsm4(sta ^ (b << 4), v0, v1, v2, v3);
    float* a = A + H * 32 + 4 * b;
    a[0] = bf_lo(v0); a[1] = bf_hi(v0); a[2] = bf_lo(v1); a[3] = bf_hi(v1);
    a[4] = bf_lo(v2); a[5] = bf_hi(v2); a[6] = bf_lo(v3); a[7] = bf_hi(v3);
  }
#pragma unroll
  for (int i = 0; i < 32; i++) keep(A[H * 32 + i]);
}
__device__ __forceinline__ void stats_acc(const Ctx& c, int h, Stats& t) {
  const uint32_t sta = (stg_base(warp_rows(c), pin(c.lane)) ^ ((h & 1) << 6)) + (h >> 1) * 16384;
  uint32_t v[8];
#pragma unroll
  for (int b = 0; b < 2; b++) ldsm4(sta ^ (b << 5), v[4 * b], v[4 * b + 1], v[4 * b + 2], v[4 * b + 3]);
#pragma unroll
  for (int i = 0; i < 8; i += 2) {
    const float a = bf_lo(v[i]), b = bf_hi(v[i]), d = bf_lo(v[i + 1]), e = bf_hi(v[i + 1]);
    t.a.x += a + b; t.b.x = fmaf(a, a, fmaf(b, b, t.b.x));
    t.a.y += d + e; t.b.y = fmaf(d, d, fmaf(e, e, t.b.y));
  }
}
__device__ __forceinline__ void stats_store(const Ctx& c, const Stats& t, uint32_t tag) {
  const int lane = pin(c.lane), rh = lane & 1;
  float sum = (rh ? t.a.y : t.a.x) + __shfl_xor_sync(0xffffffffu, rh ? t.a.x : t.a.y, 1);
  float sq = (rh ? t.b.y : t.b.x) + __shfl_xor_sync(0xffffffffu, rh ? t.b.x : t.b.y, 1);
  sum += __shfl_xor_sync(0xffffffffu, sum, 2);
  sq += __shfl_xor_sync(0xffffffffu, sq, 2);
  const float mu = sum * (1.f / 128.f), m2 = fmaxf(fmaf(-mu, sum, sq), 0.f);
  if (!(lane & 2))
    st_b64(c.p.s->stats + pin(c.jc) * SEQ + pin(c.rb) * 128 + pin(c.w) * 16 + (lane >> 2) + rh * 8,
           (__float_as_uint(mu) & ~1u) | (tag & 1), (__float_as_uint(m2) & ~1u) | (tag >> 1));
}
__device__ __forceinline__ void store_box(const Ctx& c, __nv_bfloat16* g, int h) {
  const int lane = pin(c.lane), r = lane >> 3, ch = lane & 7;
  const uint32_t rows = warp_rows(c) + r * 128 + h * 16384;
  g += (size_t)seq_row(c, r) * DM + pin(c.jc) * 128 + h * 64 + ch * 8;
  uint4 v[4];
#pragma unroll
  for (int i = 0; i < 4; i++) v[i] = lds128(rows + i * 512 + ((ch ^ ((r + 4 * i) & 7)) << 4));
#pragma unroll
  for (int i = 0; i < 4; i++) stg128(g + i * 8 * DM, v[i].x, v[i].y, v[i].z, v[i].w);
}
template <int H>
__device__ __forceinline__ void stage_box(uint32_t sta, const float (&A)[64]) {
#pragma unroll
  for (int b = 8 * H; b < 8 * H + 8; b += 2)
    stsm4((sta ^ ((b & 7) << 4)) + H * 16384, pack_bf16(A[4 * b], A[4 * b + 1]), pack_bf16(A[4 * b + 2], A[4 * b + 3]),
          pack_bf16(A[4 * b + 4], A[4 * b + 5]), pack_bf16(A[4 * b + 6], A[4 * b + 7]));
}
__device__ __forceinline__ void finish_x(Ctx& c, float (&A)[64], __nv_bfloat16* g) {
  const uint32_t sta = stg_base(warp_rows(c), pin(c.lane));
  wgmma_wait<0>();
  release(c);
  if (c.it == 2 * NST) cluster_arrive();
  keep_all(A);
  stage_box<0>(sta, A);
  __syncwarp();
  store_box(c, g, 0);
  carrive(c, B_DONE + c.wg * 8);
  stage_box<1>(sta, A);
  fence_proxy_async_smem();
  carrive(c, B_BOX1);
  bar_sync(2 + c.wg, 128);
}

struct Att { uint32_t q[16], k[16], kp[8], p[2][4], vp[8], vf[16]; float s[2][3][4], v[4][2], o[8][4]; };
struct Cs { float4 v[4]; };
__device__ __forceinline__ uint32_t vswz(int r) { return ((r & 1) << 2) | ((r >> 1) & 3); }
__device__ __forceinline__ uint32_t kv_base(const Ctx& c) { return c.sb + KV_OFF + (pin(c.w) >> 2) * KV_WG; }
__device__ __forceinline__ uint4* halo_ptr(const Params& p, int lp, int s, int rb, int jc, int wg, int lane) {
  return p.s->halo + (size_t)((((lp * 2 + s) * 16 + rb) * 8 + jc) * 2 + wg) * (5 * 32) + lane;
}
__device__ __forceinline__ void load_cs(const Ctx& c, int i, Cs& cs) {
  const uint32_t a = c.sb + CSQ_OFF + i * 256 + (pin(c.lane) & 3) * 16;
#pragma unroll
  for (int j = 0; j < 4; j++) cs.v[j] = lds128f(a + j * 64);
}
template <int B, bool KEEP>
__device__ __forceinline__ void fix_box(const Ctx& c, float (&acc)[96], const Cs& cs) {
#pragma unroll
  for (int j = 0; j < 4; j++) {
    float* a = acc + 32 * B + 8 * j;
    a[0] -= c.m0 * cs.v[j].x; a[1] -= c.m0 * cs.v[j].y; a[2] -= c.m1 * cs.v[j].x; a[3] -= c.m1 * cs.v[j].y;
    a[4] -= c.m0 * cs.v[j].z; a[5] -= c.m0 * cs.v[j].w; a[6] -= c.m1 * cs.v[j].z; a[7] -= c.m1 * cs.v[j].w;
  }
#pragma unroll
  for (int i = 0; i < 32; i++) if (KEEP) keep(acc[32 * B + i]);
}
template <int B>
__device__ __forceinline__ void pack_box(const float (&acc)[96], uint32_t (&f)[16]) {
#pragma unroll
  for (int i = 0; i < 16; i++) { f[i] = pack_bf16(acc[32 * B + 2 * i], acc[32 * B + 2 * i + 1]); keep(f[i]); }
}
__device__ __forceinline__ void halo_send(const Ctx& c, int s, int part, uint32_t (&f)[16]) {
  uint4* hp = halo_ptr(c.p, c.lp, s, pin(c.rb), pin(c.jc), c.wg, pin(c.lane)) + part * 64;
  f[7] = f[7] ? f[7] : 0x8000u;
  f[15] = f[15] ? f[15] : 0x8000u;
  st_tag_if(c.wi == 3, hp, f[1], f[3], f[5], f[7]);
  st_tag_if(c.wi == 3, hp + 32, f[9], f[11], f[13], f[15]);
}
__device__ __forceinline__ void halo_clear(const Ctx& c, int s) {
  uint4* hp = halo_ptr(c.p, c.lp, s, pin(c.rb), pin(c.jc), c.wg, pin(c.lane));
#pragma unroll
  for (int i = 0; i < 4; i++) st_tag_if(c.wi == 3, hp + i * 32, 0u, 0u, 0u, 0u);
  if (!s) st_tag_if(c.wi == 3, hp + 128, __float_as_uint(c.r1), 1u, 1u, 1u);
}
__device__ __forceinline__ void put_k(const Ctx& c, const uint32_t (&k)[16]) {
  const uint32_t a = kv_base(c) + KV_K + 1024 + c.wi * 1024 + pin(c.lane) * 16;
  sts128(a, k[1], k[3], k[5], k[7]);
  sts128(a + 512, k[9], k[11], k[13], k[15]);
}
__device__ __forceinline__ void put_v(const Ctx& c, const uint32_t (&v)[16]) {
  const int lane = pin(c.lane), g = lane >> 2;
  const uint32_t a = kv_base(c) + (8 + c.wi * 16 + g) * 128 + (((lane & 3) ^ vswz(g)) << 4);
#pragma unroll
  for (int i = 0; i < 4; i++) {
    const int hh = i >> 1, rh = i & 1;
    sts128((a ^ (hh << 6)) + rh * 1024, v[8 * hh + rh], v[8 * hh + 2 + rh], v[8 * hh + 4 + rh], v[8 * hh + 6 + rh]);
  }
}
__device__ __forceinline__ void put_rstd(const Ctx& c) {
  const int lane = pin(c.lane);
  if (!(lane & 2)) sts32f(kv_base(c) + KV_R + (8 + c.wi * 16 + (lane & 1) * 8 + (lane >> 2)) * 4, (lane & 1) ? c.r1 : c.r0);
}
__device__ __forceinline__ void get_rstd(const Ctx& c, float (&rk)[4]) {
  const int lane = pin(c.lane), g = lane >> 2, j = 2 * (lane & 3);
  const uint32_t a = kv_base(c) + KV_R + (c.wi * 16 + j) * 4, a0 = a + (j <= g ? 32 : 0), a1 = a + (j + 1 <= g ? 36 : 4);
  rk[0] = lds32f(a0); rk[1] = lds32f(a1); rk[2] = lds32f(a0 + 32); rk[3] = lds32f(a1 + 32);
}
__device__ __forceinline__ void halo_wait(const Ctx& c, int s) {
  if (c.wi == 0) mbar_wait(c.sb + MISC_OFF + B_HALO + c.wg * 8, s);
}
__device__ __forceinline__ void att_ldk(const Ctx& c, Att& t) {
  const uint32_t a = kv_base(c) + KV_K + c.wi * 1024 + pin(c.lane) * 16;
  const uint4 u = lds128(a), v = lds128(a + 512);
  t.kp[0] = u.x; t.kp[1] = u.y; t.kp[2] = u.z; t.kp[3] = u.w; t.kp[4] = v.x; t.kp[5] = v.y; t.kp[6] = v.z; t.kp[7] = v.w;
}
template <int W>
__device__ __forceinline__ void att_ldv(const Ctx& c, Att& t) {
  const int lane = pin(c.lane);
  const uint32_t vb = kv_base(c) + c.wi * 2048, sw = vswz(lane & 7);
  if (W & 2) {
    const uint32_t ap = vb + (lane & 7) * 128 + (((lane >> 3) ^ sw) << 4);
    ldsm4t(ap, t.vp[0], t.vp[1], t.vp[2], t.vp[3]);
    ldsm4t(ap ^ 64, t.vp[4], t.vp[5], t.vp[6], t.vp[7]);
  }
  if (W & 1) {
    const uint32_t ao = vb + 1024 + (lane & 15) * 128 + (((lane >> 4) ^ sw) << 4);
#pragma unroll
    for (int b = 0; b < 8; b += 2) ldsm4t(ao ^ (b << 4), t.vf[2 * b], t.vf[2 * b + 1], t.vf[2 * b + 2], t.vf[2 * b + 3]);
  }
}
template <int W>
__device__ __forceinline__ void att_s(Att& t) {
#pragma unroll
  for (int ks = 0; ks < 2; ks++)
#pragma unroll
    for (int i = (W & 1) ? 0 : 4; i < ((W & 2) ? 6 : 4); i++) {
      const int hh = i & 1, kb = 2 - (i >> 1);
      const uint32_t* q = t.q + 8 * hh + 4 * ks;
      const uint32_t b0 = kb ? t.k[8 * hh + 4 * ks + kb - 1] : t.kp[4 * hh + 2 * ks], b1 = kb ? t.k[8 * hh + 4 * ks + kb + 1] : t.kp[4 * hh + 2 * ks + 1];
      if (ks) mma16816(t.s[hh][kb], q[0], q[1], q[2], q[3], b0, b1); else mma16816z(t.s[hh][kb], q[0], q[1], q[2], q[3], b0, b1);
    }
}
__device__ __forceinline__ void att_exp(const Ctx& c, Att& t, const float (&rk)[4]) {
  const int lane = pin(c.lane), g = lane >> 2, j = 2 * (lane & 3);
  const bool u0 = j <= g, u1 = j + 1 <= g, first = c.rb == 0 && c.wi == 0;
  const float sc = 0.17677669529663687f * 1.4426950408889634f;
  const float c0 = sc * c.r0, c1 = sc * c.r1;
  const float b0 = (first && !u0) ? -INFINITY : 0.f, b1 = (first && !u1) ? -INFINITY : 0.f;
  float m[4];
#pragma unroll
  for (int hh = 0; hh < 2; hh++) {
    t.v[2 * hh][0] = fmaf(u0 ? t.s[hh][1][0] : t.s[hh][0][0], c0 * rk[0], b0);
    t.v[2 * hh][1] = fmaf(u1 ? t.s[hh][1][1] : t.s[hh][0][1], c0 * rk[1], b1);
    t.v[2 * hh + 1][0] = (u0 ? t.s[hh][2][2] : t.s[hh][1][2]) * (c1 * rk[2]);
    t.v[2 * hh + 1][1] = (u1 ? t.s[hh][2][3] : t.s[hh][1][3]) * (c1 * rk[3]);
  }
#pragma unroll
  for (int i = 0; i < 4; i++) m[i] = fmaxf(t.v[i][0], t.v[i][1]);
#pragma unroll
  for (int o = 1; o <= 2; o <<= 1)
#pragma unroll
    for (int i = 0; i < 4; i++) m[i] = fmaxf(m[i], __shfl_xor_sync(0xffffffffu, m[i], o));
#pragma unroll
  for (int i = 0; i < 4; i++) {
    t.v[i][0] = ex2(t.v[i][0] - m[i]);
    t.v[i][1] = ex2(t.v[i][1] - m[i]);
    keep(t.v[i][0]);
    keep(t.v[i][1]);
  }
}
__device__ __forceinline__ void att_p(const Ctx& c, Att& t, const float (&rk)[4]) {
  const int lane = pin(c.lane), g = lane >> 2, j = 2 * (lane & 3);
  float m[4];
#pragma unroll
  for (int i = 0; i < 4; i++) m[i] = t.v[i][0] + t.v[i][1];
#pragma unroll
  for (int o = 1; o <= 2; o <<= 1)
#pragma unroll
    for (int i = 0; i < 4; i++) m[i] += __shfl_xor_sync(0xffffffffu, m[i], o);
  const uint32_t mu = (j <= g ? 0xffffu : 0u) | (j + 1 <= g ? 0xffff0000u : 0u);
#pragma unroll
  for (int i = 0; i < 4; i++) {
    const float inv = rcp(m[i]);
    const uint32_t pp = pack_bf16(t.v[i][0] * rk[2 * (i & 1)] * inv, t.v[i][1] * rk[2 * (i & 1) + 1] * inv);
    t.p[i >> 1][(i & 1) * 2] = pp & ~mu;
    t.p[i >> 1][(i & 1) * 2 + 1] = pp & mu;
    keep(t.p[i >> 1][(i & 1) * 2]);
    keep(t.p[i >> 1][(i & 1) * 2 + 1]);
  }
}
__device__ __forceinline__ void att_pv(Att& t) {
#pragma unroll
  for (int b = 0; b < 8; b++) mma1688z(t.o[b], t.p[b >> 2][0], t.vp[b]);
#pragma unroll
  for (int b = 0; b < 8; b++) mma16816(t.o[b], t.p[b >> 2][1], t.p[b >> 2][2], 0u, t.p[b >> 2][3], t.vf[2 * b], t.vf[2 * b + 1]);
}
template <bool LOCAL>
__device__ __forceinline__ void att_out(const Ctx& c, int s, const Att& t) {
  const int lane = pin(c.lane), g = lane >> 2, tq = lane & 3;
  __nv_bfloat16* dst = c.p.s->o + (size_t)seq_row(c, g) * DM + (s * 8 + pin(c.jc)) * 64 + tq * 8;
  const uint32_t la = warp_rows(c) + g * 128 + ((tq ^ g) << 4);
  uint32_t v[16];
#pragma unroll
  for (int i = 0; i < 4; i++) {
    const int hh = i & 1, rh = i >> 1;
#pragma unroll
    for (int b = 0; b < 4; b++) v[4 * i + b] = pack_bf16(t.o[4 * hh + b][2 * rh], t.o[4 * hh + b][2 * rh + 1]);
  }
#pragma unroll
  for (int i = 0; i < 4; i++) stg128(dst + (i >> 1) * 16 * DM + (i & 1) * 32, v[4 * i], v[4 * i + 1], v[4 * i + 2], v[4 * i + 3]);
  carrive(c, B_DONE + c.wg * 8);
  if (LOCAL) {
#pragma unroll
    for (int i = 0; i < 4; i++) sts128((la ^ ((i & 1) << 6)) + (i >> 1) * 1024, v[4 * i], v[4 * i + 1], v[4 * i + 2], v[4 * i + 3]);
  }
}
__device__ __forceinline__ void halo_go(const Ctx& c) {
  if (c.wi == 0 && c.lane == 0) mbar_arrive(c.sb + MISC_OFF + B_HGO + c.wg * 8);
}

__device__ __forceinline__ void phase_a(Ctx& c, Stage& s) {
  float O[64];
  const uint32_t misc = c.sb + MISC_OFF, stag = c.lp * 2 + 1;
  Att t;
  float rk[4];
  {
    float U[96], V[96];
    step1<true, true>(c, s, V, Nop());
    step1<false, false>(c, s, V, Nop());
    step1<true, false>(c, s, U, Nop());
    {
      Stats st;
      st.a = st.b = st.c = st.d = make_float2(0.f, 0.f);
#pragma unroll 1
      for (int k = 0; k < 11; k++)
        step1<false, false, 2>(c, s, U, [&]() {
          if (k == 2) mbar_wait(misc + B_XL, 0);
          if (k >= 3 && k < 7) stats_acc(c, k - 3, st);
          if (k == 6) stats_store(c, st, stag);
          if (k == 9) load_stats(c, st);
        });
      step1<false, false>(c, s, U, [&]() { combine_stats(c, st, stag); mbar_wait(misc + B_CSQ + 8, 0); });
    }
#pragma unroll 1
    for (int k = 0; k < 3; k++) {
      Cs cs;
      load_cs(c, 3 + k, cs);
      step1<false, false, 2>(c, s, U, [&]() {
        if (k & 2) { fix_box<2, true>(c, V, cs); mbar_wait(misc + B_CSQ, 0); }
        else if (k & 1) fix_box<1, true>(c, V, cs);
        else { halo_clear(c, 0); fix_box<0, true>(c, V, cs); }
      });
    }
    {
      Cs cs;
      load_cs(c, 1, cs);
      step1<false, false>(c, s, V, [&]() { keep_all(U); fix_box<1, false>(c, U, cs); pack_box<1>(U, t.k); halo_send(c, 0, 0, t.k); put_k(c, t.k); });
      step1<false, false>(c, s, V, [&]() { load_cs(c, 2, cs); fix_box<2, false>(c, U, cs); pack_box<2>(U, t.vf); halo_send(c, 0, 1, t.vf); put_v(c, t.vf); load_cs(c, 0, cs); halo_go(c); });
      step1<false, false>(c, s, V, [&]() { fix_box<0, false>(c, U, cs); pack_box<0>(U, t.q); put_rstd(c); });
    }
    step1<false, false>(c, s, V, [&]() { halo_clear(c, 1); });
    step1<false, false>(c, s, V, [&]() { bar_sync(2 + c.wg, 128); halo_wait(c, 0); att_ldk(c, t); get_rstd(c, rk); });
    att_s<3>(t);
    step1<false, false>(c, s, V, [&]() { att_exp(c, t, rk); });
    step1<false, false>(c, s, V, [&]() { att_ldv<3>(c, t); att_p(c, t, rk); });
    att_pv(t);
    step1<false, false>(c, s, V, [&]() { att_out<false>(c, 0, t); });
    step1<false, false>(c, s, V, [&]() { resid_init<0>(c, O); });
    step1<false, false>(c, s, V, [&]() { resid_init<1>(c, O); });
#pragma unroll 1
    for (int k = 0; k < 4; k++) step1<false, false>(c, s, V, Nop());
    wgmma_wait<0>();
    release(c);
    keep_all(V);
    pack_box<1>(V, t.k); halo_send(c, 1, 0, t.k); put_k(c, t.k);
    pack_box<2>(V, t.vf); halo_send(c, 1, 1, t.vf); put_v(c, t.vf);
    pack_box<0>(V, t.q);
  }
  step1<false, true, 2>(c, s, O, [&]() { halo_go(c); });
  step1<false, false>(c, s, O, Nop());
  wgmma_wait<0>();
  release(c);
  bar_sync(1, 256);
  cut(s);
  att_ldv<1>(c, t);
  att_s<1>(t);
  halo_wait(c, 1);
  att_ldk(c, t);
  att_ldv<2>(c, t);
  att_s<2>(t);
  att_exp(c, t, rk);
  att_p(c, t, rk);
  att_pv(t);
  att_out<true>(c, 1, t);
  bar_sync(1, 256);
  step1<false, true>(c, s, O, Nop());
#pragma unroll 1
  for (int k = NOA + 1; k < 16; k++)
    step1<false, false, 2>(c, s, O, [&]() {
      if (k == 6) { fence_proxy_async_smem(); bar_sync(2 + c.wg, 128); }
    });
  finish_x(c, O, c.p.s->x);
}

template <int H>
__device__ __forceinline__ void scale_to(const Ctx& c, float (&E)[64], float (&A)[64]) {
  const float h0 = 0.5f * c.r0, h1 = 0.5f * c.r1;
#pragma unroll
  for (int i = (H & 1) ? 0 : 32; i < ((H & 2) ? 64 : 32); i++) {
    keep(A[i]);
    E[i] = A[i] * (i < 32 ? ((i & 2) ? h1 : h0) : ((i & 2) ? c.r1 : c.r0));
    keep(E[i]);
  }
}
template <int B>
__device__ __forceinline__ void piece(const Ctx& c, float (&A)[64], const float4 cs) {
  float h[4];
#pragma unroll
  for (int e = 0; e < 4; e++) {
    const float n = (e & 2) ? c.m1 : c.m0;
    const float a = fmaf(n, (e & 1) ? cs.y : cs.x, A[4 * B + e]), u = fmaf(n, (e & 1) ? cs.w : cs.z, A[32 + 4 * B + e]);
    const float w = a * u;
    h[e] = fmaf(w, tanh_approx(a), w);
  }
  A[4 * B] = __uint_as_float(pack_bf16(h[0], h[1]));
  A[4 * B + 1] = __uint_as_float(pack_bf16(h[2], h[3]));
  if (B == 7) carrive(c, B_CSFREE);
}
template <int B>
__device__ __forceinline__ void piece2(const Ctx& c, float (&E)[64], const float4 c0, const float4 c1) {
  piece<B>(c, E, c0);
  piece<B + 1>(c, E, c1);
}
template <int Q>
__device__ __forceinline__ void store_h2(const Ctx& c, const float (&E)[64], int blk) {
  const int lane = pin(c.lane);
  __nv_bfloat16* dst = c.p.s->h + (size_t)seq_row(c, lane >> 2) * FF + (blk * 8 + pin(c.jc)) * 64 + Q * 32 + (lane & 3) * 8;
#pragma unroll
  for (int rh = 0; rh < 2; rh++)
    stg128(dst + rh * 16 * FF, __float_as_uint(E[16 * Q + rh]), __float_as_uint(E[16 * Q + 4 + rh]),
           __float_as_uint(E[16 * Q + 8 + rh]), __float_as_uint(E[16 * Q + 12 + rh]));
}
__device__ __forceinline__ void tail_piece(const Ctx& c, float (&A)[64], const float4 cs, int k, int blk) {
  if (k < 4) {
    if (k < 2) { if (k == 0) piece<0>(c, A, cs); else piece<1>(c, A, cs); }
    else { if (k == 2) piece<2>(c, A, cs); else { piece<3>(c, A, cs); store_h2<0>(c, A, blk); } }
  } else {
    if (k < 6) { if (k == 4) piece<4>(c, A, cs); else piece<5>(c, A, cs); }
    else { if (k == 6) piece<6>(c, A, cs); else { piece<7>(c, A, cs); store_h2<1>(c, A, blk); } }
  }
}
template <int LOFF>
__device__ __forceinline__ void drain(Ctx& c, Stage& s, float (&L)[64], float (&M)[64], float (&E)[64]) {
  wait_full(c);
  wgmma_fence();
  stage128<false>(M, s.da, s.db + (1024 - LOFF));
  wgmma_commit();
  wgmma_wait<1>();
  release(c);
  scale_to<3>(c, E, L);
  wgmma_fence();
  stage128<true>(L, s.da, s.db + LOFF);
  wgmma_commit();
  s = peek(c);
}
__device__ __forceinline__ void phase_b(Ctx& c, Stage& s) {
  float X[64], Y[64], E[64];
  const uint32_t stag = (c.lp * 2 + 2) & 3;
  step1<true, true>(c, s, X, Nop());
  step1<false, false>(c, s, X, Nop());
  {
    Stats st;
    st.a = st.b = st.c = st.d = make_float2(0.f, 0.f);
    step2<true>(c, s, E, Y, Nop());
#pragma unroll 1
    for (int k = 0; k < 8; k++)
      step2<false, 2>(c, s, E, Y, [&]() {
        if (k < 4) stats_acc(c, k, st);
        if (k == 3) stats_store(c, st, stag);
        if (k == 5) load_stats(c, st);
        if (k == 7) { combine_stats(c, st, stag); c.m0 *= -c.r0; c.m1 *= -c.r1; }
      });
  }
#pragma unroll 1
  for (int k = 0; k < 7; k++) step1<false, false>(c, s, E, Nop());
  step2<false, 0>(c, s, X, Y, [&]() { scale_to<3>(c, E, E); });
#pragma unroll 1
  for (int blk = 0;; blk++) {
    mbar_wait(c.sb + MISC_OFF + B_CS, (blk + c.lp) & 1);
    const int n = blk == 2 ? 8 : 6;
#pragma unroll 1
    for (int k = 0; k < n; k++) {
      const uint32_t ca = c.sb + CSG_OFF + (k & 3) * 128 + (pin(c.lane) & 3) * 16;
      const float4 c0 = lds128f(ca), c1 = lds128f(ca + 64);
      step2<false, 2>(c, s, X, Y, [&]() {
        if (k & 4) {
          if (!(k & 3)) store_h2<0>(c, E, blk);
          else if (k == 5) { store_h2<1>(c, E, blk); if (blk == 3) carrive(c, B_DONE + c.wg * 8); }
        } else if (k & 2) {
          if (k & 1) piece2<6>(c, E, c0, c1); else piece2<4>(c, E, c0, c1);
        } else {
          if (k & 1) piece2<2>(c, E, c0, c1); else piece2<0>(c, E, c0, c1);
        }
      });
    }
    if (blk == 4) break;
    if (blk & 1) drain<0>(c, s, X, Y, E); else drain<1024>(c, s, Y, X, E);
  }
  step2<false>(c, s, X, Y, [&]() { resid_init<0>(c, E); });
  step2<false>(c, s, X, Y, [&]() { resid_init<1>(c, E); mbar_wait(c.sb + MISC_OFF + B_CS, (5 + c.lp) & 1); });
  step1<false, false>(c, s, X, [&]() { scale_to<1>(c, Y, Y); });
  step1<false, false>(c, s, X, [&]() { scale_to<2>(c, Y, Y); });
#pragma unroll 1
  for (int blk = 5;; blk++) {
#pragma unroll 1
    for (int k = 0; k < 8; k++) {
      const float4 cs = lds128f(c.sb + CSG_OFF + k * 64 + (pin(c.lane) & 3) * 16);
      if (blk == 5 && k < 5) step1<false, false, 0>(c, s, X, Nop()); else step1<false, false, 0>(c, s, E, Nop());
      tail_piece(c, Y, cs, k, blk);
      wgmma_wait<1>();
    }
    if (blk == 6) break;
    step1<false, false>(c, s, E, [&]() { scale_to<1>(c, Y, X); });
    step1<false, false>(c, s, E, [&]() { scale_to<2>(c, Y, X); mbar_wait(c.sb + MISC_OFF + B_CS, c.lp & 1); });
  }
  carrive(c, B_DONE + c.wg * 8);
#pragma unroll 1
  for (int k = 0; k < 43; k++) step1<false, false>(c, s, E, Nop());
  finish_x(c, E, c.lp ? c.p.out : c.p.s->x);
}

__device__ __forceinline__ void acc8(float (&a)[8], const uint4& v) {
  a[0] += bf_lo(v.x); a[1] += bf_hi(v.x); a[2] += bf_lo(v.y); a[3] += bf_hi(v.y);
  a[4] += bf_lo(v.z); a[5] += bf_hi(v.z); a[6] += bf_lo(v.w); a[7] += bf_hi(v.w);
}
__device__ __forceinline__ void st_sums(uint4* dst, const float (&a)[8], uint32_t tag) {
  uint32_t u[8];
#pragma unroll
  for (int i = 0; i < 8; i++) u[i] = (__float_as_uint(a[i]) & ~1u) | ((tag >> (i & 3)) & 1u);
  st_tag(dst, u[0], u[1], u[2], u[3]);
  st_tag(dst + 1, u[4], u[5], u[6], u[7]);
}
__device__ __forceinline__ bool add_sum(float4& a, const uint4& v, uint32_t tag) {
  a.x += __uint_as_float(v.x & ~1u); a.y += __uint_as_float(v.y & ~1u);
  a.z += __uint_as_float(v.z & ~1u); a.w += __uint_as_float(v.w & ~1u);
  return ((v.x & 1) | (v.y & 1) << 1 | (v.z & 1) << 2 | (v.w & 1) << 3) == (tag & 15);
}

__device__ __forceinline__ void spare_sum(const Params& p, uint32_t sb, int d, int w, int lane) {
  const int chunk = (w & 1) * 4 + (lane & 3), rg = lane >> 2;
  const uint32_t base = sb + (w >> 1) * 8192 + rg * 128 + ((chunk ^ rg) << 4);
  uint32_t slot = 0, par = 0;
#pragma unroll 1
  for (int t = d; t < 28; t += 4) {
    float a[8] = {0, 0, 0, 0, 0, 0, 0, 0};
#pragma unroll 1
    for (int k = 0; k < 16; k++) {
      mbar_wait_idle(sb + MISC_OFF + B_SFULL + slot * 8, par);
      uint4 v[8];
#pragma unroll
      for (int r = 0; r < 8; r++) v[r] = lds128(base + slot * 32768 + r * 1024);
#pragma unroll
      for (int r = 0; r < 8; r++) acc8(a, v[r]);
      __syncwarp();
      if (lane == 0) mbar_arrive(sb + MISC_OFF + B_SEMPTY + slot * 8);
      if (++slot == 6) { slot = 0; par ^= 1; }
    }
#pragma unroll 1
    for (int o = 16; o >= 4; o >>= 1)
#pragma unroll
      for (int i = 0; i < 8; i++) a[i] += __shfl_xor_sync(0xffffffffu, a[i], o);
    if (lane < 4) st_sums(p.s->part + (3 * DM + ((w >> 1) & 1) * FF + t * 128 + (w >> 2) * 64 + (w & 1) * 32) / 4 + lane * 2, a, ld_tag_s(sb));
  }
}
__device__ __forceinline__ void spare_load(const Params& p, uint32_t sb, int d, int lane) {
  uint32_t slot = 0, par = 1;
  const uint32_t want = ld_epoch(p) * 2 + 1, t0 = clock();
  while ((uint32_t)clock() - t0 < 13000) __nanosleep(200);
#pragma unroll 1
  for (int t = d; t < 28; t += 4) {
    if ((t >> 2) == 2) {
#pragma unroll 1
      for (uint32_t i = 0, n = 0; i < 4;) {
        const uint32_t v = ld_flag(reinterpret_cast<const uint8_t*>(p.s->flags + (i * 4 + (lane >> 3)) * 8 + F_X1B - 1) + (lane & 7) * 2);
        if (__all_sync(0xffffffffu, ((v - want) & 255) < 2)) i++; else __nanosleep(300);
        if (++n > (1u << 20)) __trap();
      }
    }
#pragma unroll 1
    for (int k = 0; k < 16; k++) {
      const uint32_t bar = sb + MISC_OFF + B_SFULL + slot * 8;
      mbar_wait(sb + MISC_OFF + B_SEMPTY + slot * 8, par);
      if (elect_one()) {
        mbar_expect_tx(bar, 32768);
#pragma unroll
        for (int b = 0; b < 4; b++) tma_load(sb + slot * 32768 + b * 8192, (b & 1) ? &p.wu : &p.wg, bar, t * 128 + (b >> 1) * 64, k * 64);
      }
      if (++slot == 6) { slot = 0; par ^= 1; }
    }
  }
}
__device__ __forceinline__ uint32_t qkv_sums(const Params& p, uint32_t sb, int q, int rb, int jc, int lane) {
  const uint32_t bar = sb + MISC_OFF + B_SLAB + q * 8, buf = sb + KV_OFF + q * 8192;
  const uint32_t tag = ld_epoch(p) + 1;
  mbar_wait_idle(sb + MISC_OFF + B_FULL, 0);
  const uint32_t t0 = clock();
  if (q == 0) {
    const int gx = (jc >> 1) - 1;
    if (gx >= 0) mbar_wait_idle(sb + MISC_OFF + B_EMPTY + gx * 8, 0);
    if (elect_one()) {
      mbar_expect_tx(sb + MISC_OFF + B_XL, 32768);
      tma_load3(sb + STG_OFF, &p.x0, sb + MISC_OFF + B_XL, jc * 128, rb * 64);
      tma_load3(sb + STG_OFF + 16384, &p.x0, sb + MISC_OFF + B_XL, jc * 128 + 64, rb * 64);
    }
  }
  {
    const int col = q * DM + ((rb & 1) * 8 + jc) * 64;
    float a[8] = {0.f, 0.f, 0.f, 0.f, 0.f, 0.f, 0.f, 0.f};
#pragma unroll 1
    for (int h = 0; h < 2; h++) {
      while (h && (uint32_t)clock() - t0 < 4600) __nanosleep(100);
      if (elect_one()) {
        mbar_expect_tx(bar, 8192);
        tma_load(buf, &p.wqkv, bar, col, ((rb & 14) + h) * 64);
        tma_load(buf + 4096, &p.wqkv, bar, col, ((rb & 14) + h) * 64 + 32);
      }
      mbar_wait_idle(bar, h);
      const uint32_t base = buf + (lane >> 3) * 128 + (((lane & 7) ^ (lane >> 3)) << 4);
#pragma unroll 1
      for (int r = 0; r < 8; r += 2) {
        const uint4 v0 = lds128(base + r * 1024), v1 = lds128((base ^ 64) + r * 1024 + 512);
        const uint4 v2 = lds128(base + r * 1024 + 1024), v3 = lds128((base ^ 64) + r * 1024 + 1536);
        acc8(a, v0); acc8(a, v1); acc8(a, v2); acc8(a, v3);
      }
      fence_proxy_async_smem();
      __syncwarp();
    }
#pragma unroll 1
    for (int o = 8; o <= 16; o <<= 1)
#pragma unroll
      for (int j = 0; j < 8; j++) a[j] += __shfl_xor_sync(0xffffffffu, a[j], o);
    if (lane < 8) st_sums(p.s->part + ((rb >> 1) * NCS + col) / 4 + lane * 2, a, tag);
  }
#pragma unroll 1
  for (int s = 1; s >= 0; s--) {
    const uint4* src = p.s->part + ((lane >> 4) * 4 * NCS + q * DM + (s * 8 + jc) * 64) / 4 + (lane & 15);
    float4 a;
    uint32_t n = 0;
    while (true) {
      uint4 v[4];
#pragma unroll
      for (int r = 0; r < 4; r++) v[r] = ld_tag(src + r * (NCS / 4));
      a = make_float4(0.f, 0.f, 0.f, 0.f);
      bool ok = true;
#pragma unroll
      for (int r = 0; r < 4; r++) ok = add_sum(a, v[r], tag) && ok;
      if (__all_sync(0xffffffffu, ok)) break;
      if (++n > (1u << 18)) __trap();
    }
    a.x += __shfl_xor_sync(0xffffffffu, a.x, 16); a.y += __shfl_xor_sync(0xffffffffu, a.y, 16);
    a.z += __shfl_xor_sync(0xffffffffu, a.z, 16); a.w += __shfl_xor_sync(0xffffffffu, a.w, 16);
    const uint32_t dst = sb + CSQ_OFF + (s * 3 + q) * 256 + ((lane & 15) >> 2) * 64 + (lane & 1) * 32 + (lane & 2) * 4 + (lane >> 4) * 16;
    sts64f(dst, lane < 16 ? a.x : a.z, lane < 16 ? a.y : a.w);
    __syncwarp();
    if (lane == 0) mbar_arrive(sb + MISC_OFF + B_CSQ + s * 8);
  }
  return tag;
}

struct Prod {
  const Params& p;
  uint32_t sb, it;
  uint32_t seq, kb, kinc;
};
__device__ __forceinline__ uint32_t seg_begin(Prod& pr, int sg, int jc) {
  const uint32_t d = pr.p.t.seg[sg], ks = (d >> 19) & 7;
  pr.seq = pr.p.t.seq[sg < 6 ? 8 : jc][ks];
  pr.kinc = ks == K_LIN;
  pr.kb = ks == K_LIN ? ((d >> 13) & 7) * 8 : 0;
  return d;
}
__device__ __forceinline__ int next_k(Prod& pr) {
  const int k = (pr.kb + (pr.seq & 15)) * 64;
  pr.seq >>= 4;
  pr.kb += pr.kinc;
  return k;
}
__device__ __forceinline__ void wait_released(const Prod& pr, uint32_t lag) {
  const uint32_t j = pr.it - lag;
  mbar_wait(pr.sb + MISC_OFF + B_EMPTY + (j & 7) * 8, (j >> 3) & 1);
}
template <int NB>
__device__ __forceinline__ void produce_b(Prod& pr, int n, uint32_t bytes, const CUtensorMap* tb, int c0, int c1, uint32_t rank,
                                          const CUtensorMap* ta, int arow) {
#pragma unroll 1
  for (; n > 0; n--) {
    const uint32_t e = pr.p.t.ring[pr.it];
    const int k = pin(next_k(pr));
    const uint32_t bar = pin(pr.sb + MISC_OFF + B_FULL + (pr.it & 7) * 8);
    const uint32_t b = pin(pr.sb + ((e >> 16) << 4) + rank * (NB == 3 ? 4096 : 8192));
    wait_released(pr, e & 15);
    if (elect_one()) {
      mbar_expect_tx(bar, bytes);
      if (NB == 3) {
#pragma unroll
        for (int q = 0; q < 3; q++) tma_load_mc(b + q * 8192, tb, bar, q * DM + c0, k + rank * 32);
        if (ta) tma_load3(pr.sb + ((e & 0x3e00) << 4), ta, bar, k, arow);
      } else if (NB == 5) {
        tma_load5_mc(b, tb, bar, c0, k >> 5);
      } else {
        tma_load_mc(b, tb, bar, c0, k);
        if (NB == 4) tma_load_mc(b + 16384, tb, bar, c1, k);
      }
    }
    pr.it++;
  }
}
__device__ __forceinline__ void cs_fill(const Params& p, uint32_t sb, int i, int jc, int lane, uint32_t tag) {
  const int blk = i >= 7 ? i - 7 : i, m = lane & 15;
  const uint4* src = p.s->part + (3 * DM + (lane >> 4) * FF + (blk * 8 + jc) * 64) / 4 + m;
  float4 a;
  uint32_t n = 0;
  while (true) {
    a = make_float4(0.f, 0.f, 0.f, 0.f);
    if (__all_sync(0xffffffffu, add_sum(a, ld_tag(src), tag))) break;
    if (++n > (1u << 18)) __trap();
    __nanosleep(500);
  }
  if (i > 0) mbar_wait_idle(sb + MISC_OFF + B_CSFREE, (i - 1) & 1);
  const float f = lane < 16 ? 0.5f : 1.f;
  const uint32_t dst = sb + CSG_OFF + m * 32 + (lane >> 4) * 8;
  sts64f(dst, a.x * f, a.y * f);
  sts64f(dst + 16, a.z * f, a.w * f);
  __syncwarp();
  if (lane == 0) mbar_arrive(sb + MISC_OFF + B_CS);
}

template <bool BY_SM>
__global__ void __cluster_dims__(2, 1, 1) __launch_bounds__(384, 1)
fused_kernel(const __grid_constant__ Params p) {
  extern __shared__ __align__(1024) uint8_t smem_raw[];
  const uint32_t sb = smem_u32(smem_raw);
  const uint32_t misc = sb + MISC_OFF;
  const int warp = __shfl_sync(0xffffffffu, threadIdx.x >> 5, 0), lane = threadIdx.x & 31;
  uint32_t smid;
  asm volatile("mov.u32 %0, %%smid;" : "=r"(smid));
  const int tpc = smid >> 1;
  const int cl = __shfl_sync(0xffffffffu, !BY_SM ? (int)blockIdx.x >> 1 : tpc < 32 ? tpc
                           : tpc < 60 ? (4 + (tpc - 32) / 7) * 8 + 1 + (tpc - 32) % 7 : tpc < 62 ? tpc + 4 : (tpc - 58) * 8, 0);
  const uint32_t rank = blockIdx.x & 1;
  const int cta = cl * 2 + rank;
  const bool spare = cta >= NCTA;
  const int rb = (7 - (cl & 7)) * 2 + rank, jc = (cl >> 3) & 7;

  if (warp < 8) {
    if (warp < 2 && elect_one()) asm volatile("prefetch.tensormap [%0];" ::"l"(warp ? &p.x0 : &p.wqkv) : "memory");
    cluster_arrive();
    uint32_t tag = ld_epoch(p) + 1;
    cluster_wait();
    asm volatile("setmaxnreg.inc.sync.aligned.u32 232;");
    asm volatile("st.shared.u32 [%0], %1;" ::"r"(misc + M_TAG), "r"(tag) : "memory");
    if (spare) {
      spare_sum(p, sb, cta - NCTA, warp, lane);
      cluster_arrive();
    } else {
      Ctx c{p};
      c.sb = sb; c.w = warp; c.wg = warp >> 2; c.wi = warp & 3; c.lane = lane; c.rb = rb; c.jc = jc;
      c.rel = c.wi == 0 && lane < 2;
      asm("mapa.shared::cluster.u32 %0, %1, %2;" : "=r"(c.ebar) : "r"(misc + B_EMPTY), "r"(lane & 1));
      c.da = (((sb + c.wg * 8192) & 0x3FFFF) >> 4) | (1u << 16);
      c.db = ((sb & 0x3FFFF) >> 4) | ((8192u >> 4) << 16);
      c.it = 0;
      Stage s = peek(c);
#pragma unroll 1
      for (c.lp = 0; c.lp < 2; c.lp++) {
        phase_a(c, s);
        phase_b(c, s);
      }
      store_box(c, p.out, 1);
    }
  } else {
    asm volatile("setmaxnreg.dec.sync.aligned.u32 40;");
    if (elect_one()) {
      if (warp == 10) {
        for (int i = 0; i < 8; i++) mbar_init(misc + B_FULL + i * 8, 1);
      } else if (warp == 9) {
        if (sb & 1023) __trap();
        for (int i = 0; i < 8; i++) mbar_init(misc + B_EMPTY + i * 8, 4);
      } else if (warp == 8) {
        for (int i = 0; i < 2; i++) { mbar_init(misc + B_DONE + i * 8, 4); mbar_init(misc + B_HGO + i * 8, 1); mbar_init(misc + B_HALO + i * 8, 1); mbar_init(misc + B_CSQ + i * 8, 3); }
        mbar_init(misc + B_CS, 1); mbar_init(misc + B_XL, 1); mbar_init(misc + B_BOX1, 8); mbar_init(misc + B_CSFREE, 8);
      } else {
        for (int i = 0; i < 6; i++) { mbar_init(misc + B_SFULL + i * 8, 1); mbar_init(misc + B_SEMPTY + i * 8, 8); }
      }
      asm volatile("fence.mbarrier_init.release.cluster;" ::: "memory");
    }
    cluster_arrive();
    if (warp == 10 && !spare && elect_one()) {
      mbar_expect_tx(misc + B_FULL, 40960);
      tma_load3(sb + ((RING0 & 0x3e00) << 4), &p.x0, misc + B_FULL, 0, rb * 64);
#pragma unroll
      for (int i = 0; i < 6; i++) tma_load(sb + ((RING0 >> 16) << 4) + i * 4096, &p.wqkv, misc + B_FULL, (i >> 1) * DM + (8 + jc) * 64, (i & 1) * 32);
#pragma unroll 1
      for (int i = 1; i < 4; i++) tma_load3(sb + ((p.t.ring[i] & 0x3e00) << 4), &p.x0, misc + B_FULL + i * 8, (i & 1) * 64, rb * 64);
    }
    cluster_wait();
    if (spare) {
      if (warp == 8) {
        spare_load(p, sb, cta - NCTA, lane);
      }
    } else if (warp == 8) {
      Prod pr{p};
      pr.sb = sb; pr.it = 0;
#pragma unroll 1
      for (int sg = 0; sg < 2 * NSEG; sg++) {
        const uint32_t d = seg_begin(pr, sg, jc);
        if (sg == 0) { pr.seq >>= 4; pr.it = 1; }
        const int n = (d & 63) - (sg == 0), nb = (d >> 6) & 7, am = (d >> 9) & 3, wm = (d >> 11) & 3;
        const CUtensorMap* tb = &p.wqkv + (wm == W_D ? 4 : wm == W_G ? 2 + rank : wm);
        const int c0 = (wm & 1) ? jc * 128 + rank * 64 : (((d >> 13) & 7) * 8 + jc) * 64, c1 = (((d >> 16) & 7) * 8 + jc) * 64;
        const uint32_t bytes = nb * 8192 + (am ? 16384 : 0);
        if (nb == 3) produce_b<3>(pr, n, bytes, tb, c0, c1, rank, sg < 6 && sg > 1 ? &p.x0 : nullptr, rb * 64);
        else if (nb == 4) produce_b<4>(pr, n, bytes, tb, c0, c1, rank, nullptr, 0);
        else if (wm == W_D) produce_b<5>(pr, n, bytes, tb, c0, c1, rank, nullptr, 0);
        else produce_b<2>(pr, n, bytes, tb, c0, c1, rank, nullptr, 0);
      }
    } else {
      const uint32_t tag = qkv_sums(p, sb, warp - 9, rb, jc, lane);
      if (warp == 10) {
        Prod pr{p};
        pr.sb = sb; pr.it = 32;
        const uint8_t* fl = reinterpret_cast<const uint8_t*>(p.s->flags + rb * 8) + (lane & 15);
        mbar_wait_idle(misc + B_DONE, 0);
        uint32_t early = ~0u;
#pragma unroll 1
        for (int sg = 6; sg < 2 * NSEG; sg++) {
          const uint32_t d = seg_begin(pr, sg, jc), dep = d >> 22, am = (d >> 9) & 3;
          if (!am) { pr.it += d & 63; early = ~0u; continue; }
          const uint32_t want = (tag * 2 - (sg < NSEG)) & 255;
          uint32_t ready = dep ? __ballot_sync(0xffffffffu, early == want) : ~0u;
          if (dep) fence_proxy_async();
#pragma unroll 1
          for (int n = d & 63; n > 0; n--) {
            const uint32_t e = pr.p.t.ring[pr.it];
            const int k = pin(next_k(pr));
            const uint32_t bar = pin(misc + B_FULL + (pr.it & 7) * 8), a = pin(sb + ((e & 0x3e00) << 4));
            if (n == 1 && (pr.p.t.seg[sg + 1] >> 22)) early = ld_flag(fl + ((pr.p.t.seg[sg + 1] >> 22) - 1) * 16);
            if (am == A_X) wait_released(pr, (e >> 4) & 15);
            if (ready != ~0u) {
              const uint32_t need = (am == A_H || n == 1) ? ~0u : 3u << (am == A_X ? (k >> 6) & 14 : (k >> 5) & 14);
              if ((ready & need) != need) {
                const uint8_t* f = fl + (dep - 1) * 16;
                uint32_t v0 = ld_flag(f);
                const uint32_t t0 = clock();
                while ((uint32_t)clock() - t0 < 120) {}
                for (uint32_t i = 0;; i++) {
                  const uint32_t v1 = ld_flag(f);
                  ready = __ballot_sync(0xffffffffu, v0 == want);
                  if ((ready & need) == need) break;
                  v0 = ld_flag(f);
                  ready = __ballot_sync(0xffffffffu, v1 == want);
                  if ((ready & need) == need) break;
                  if (i > (1u << 19)) __trap();
                }
                fence_proxy_async();
              }
            }
            if (am != A_X) wait_released(pr, (e >> 4) & 15);
            if (elect_one()) tma_load3(a, &p.x0 + am, bar, k, rb * 64);
            pr.it++;
          }
        }
      } else {
        const int w = (warp - 9) >> 1;
        int ncs = 0;
#pragma unroll 1
        for (int ev = 0; ev < 14; ev++) {
          const int layer = ev >> 3, e = ev & 7;
          if (e < 2) {
            uint4* hp = halo_ptr(p, layer, e, rb - 1, jc, w, pin(lane));
            mbar_wait_idle(misc + B_HGO + w * 8, e);
            uint4 v[5];
            uint32_t n = 0;
#pragma unroll
            for (int i = 0; i < 5; i++) v[i] = make_uint4(0, 0, 0, 0);
            while (rb > 0) {
#pragma unroll
              for (int i = 0; i < 4; i++) v[i] = ld_tag(hp + i * 32);
              if (!e) v[4] = ld_tag(hp + 128);
              if (__all_sync(0xffffffffu, v[0].w && v[1].w && v[2].w && v[3].w && (e || v[4].w))) break;
              if (++n > (1u << 18)) __trap();
            }
            const int l = pin(lane);
            const uint32_t kv = sb + KV_OFF + w * KV_WG, d0 = kv + (l >> 2) * 128 + (((l & 3) ^ vswz(l >> 2)) << 4);
            sts128(kv + KV_K + l * 16, v[0].x, v[0].y, v[0].z, v[0].w);
            sts128(kv + KV_K + 512 + l * 16, v[1].x, v[1].y, v[1].z, v[1].w);
            sts128(d0, v[2].x, v[2].y, v[2].z, v[2].w);
            sts128(d0 ^ 64, v[3].x, v[3].y, v[3].z, v[3].w);
            if (!e) sts32f(kv + KV_R + (l >> 2) * 4, __uint_as_float(v[4].x));
            __syncwarp();
            if (lane == 0) mbar_arrive(misc + B_HALO + w * 8);
          }
          if (w == 1) {
            const int c1 = ev == 2 ? 1 : e == 4 ? 5 + 7 * layer : e == 5 ? 8 + 6 * layer : 0;
#pragma unroll 1
            for (; ncs < c1; ncs++) cs_fill(p, sb, ncs, jc, lane, tag);
          }
          uint8_t* flag = reinterpret_cast<uint8_t*>(p.s->flags + rb * 8 + e) + jc * 2;
          if ((e & 3) == 3) {
            if (w == 0 && lane == 0) {
              mbar_wait(misc + B_BOX1, (ev >> 2) & 1);
              mbar_wait(misc + B_FULL + 4 * 8, ev > 3);
              tma_store3(&p.x, sb + STG_OFF + 16384, jc * 128 + 64, rb * 64);
              fence_gpu();
              st_flags(flag, tag * 2 - (ev < 6));
            }
            continue;
          }
          mbar_wait_idle(misc + B_DONE + w * 8, (ev - (ev >> 2)) & 1);
          if (lane == 0) {
            if (w == 1) {
              mbar_wait(misc + B_DONE, (ev - (ev >> 2)) & 1);
              fence_gpu();
              st_flags(flag, tag * 2 - (ev < 6));
            }
          }
          if (e < 2 && rb > 0) {
            __syncwarp();
            uint4* hp = halo_ptr(p, layer, e, rb - 1, jc, w, pin(lane));
#pragma unroll 1
            for (int i = 0; i < 5; i++) st_tag(hp + i * 32, 0u, 0u, 0u, 0u);
          }
        }
      }
    }
    __syncwarp();
    if (BY_SM) {
      uint32_t nsmid;
      asm volatile("mov.u32 %0, %%nsmid;" : "=r"(nsmid));
      if (nsmid != 132) __trap();
    }
    if (threadIdx.x == 256) p.s->epoch[blockIdx.x] = ld_tag_s(sb);
    cluster_arrive();
  }
  cluster_wait();
}

typedef CUresult (*EncodeFn)(CUtensorMap*, CUtensorMapDataType, cuuint32_t, void*, const cuuint64_t*, const cuuint64_t*,
                             const cuuint32_t*, const cuuint32_t*, CUtensorMapInterleave, CUtensorMapSwizzle,
                             CUtensorMapL2promotion, CUtensorMapFloatOOBfill);

void make_map(EncodeFn fn, CUtensorMap* m, const void* ptr, uint64_t rows, uint64_t cols, uint32_t box_rows) {
  cuuint64_t dims[2] = {cols, rows};
  cuuint64_t strides[1] = {cols * 2};
  cuuint32_t box[2] = {64, box_rows};
  cuuint32_t es[2] = {1, 1};
  fn(m, CU_TENSOR_MAP_DATA_TYPE_BFLOAT16, 2, const_cast<void*>(ptr), dims, strides, box, es, CU_TENSOR_MAP_INTERLEAVE_NONE,
     CU_TENSOR_MAP_SWIZZLE_128B, CU_TENSOR_MAP_L2_PROMOTION_L2_256B, CU_TENSOR_MAP_FLOAT_OOB_FILL_NONE);
}

void make_act_map(EncodeFn fn, CUtensorMap* m, const void* ptr, uint64_t cols) {
  cuuint64_t dims[3] = {cols, SEQ / 2, 2};
  cuuint64_t strides[2] = {cols * 4, cols * 2};
  cuuint32_t box[3] = {64, 64, 2};
  cuuint32_t es[3] = {1, 1, 1};
  fn(m, CU_TENSOR_MAP_DATA_TYPE_BFLOAT16, 3, const_cast<void*>(ptr), dims, strides, box, es, CU_TENSOR_MAP_INTERLEAVE_NONE,
     CU_TENSOR_MAP_SWIZZLE_128B, CU_TENSOR_MAP_L2_PROMOTION_L2_128B, CU_TENSOR_MAP_FLOAT_OOB_FILL_NONE);
}

}

extern "C" void kernel_launch(void* const* d_in, const int* in_sizes, int n_in, void* d_out, int out_size) {
  (void)in_sizes; (void)n_in; (void)out_size;
  EncodeFn fn = nullptr;
  cudaDriverEntryPointQueryResult qr;
  cudaGetDriverEntryPoint("cuTensorMapEncodeTiled", (void**)&fn, cudaEnableDefault, &qr);
  Params p;
  cudaGetSymbolAddress((void**)&p.s, g_s);
  p.t = make_tabs();
  make_act_map(fn, &p.x0, d_in[0], DM);
  make_act_map(fn, &p.x, p.s->x, DM);
  make_act_map(fn, &p.o, p.s->o, DM);
  make_act_map(fn, &p.h, p.s->h, FF);
  make_map(fn, &p.wqkv, d_in[1], DM, 3 * DM, 32);
  make_map(fn, &p.wo, d_in[2], DM, DM, 64);
  make_map(fn, &p.wg, d_in[4], DM, FF, 64);
  make_map(fn, &p.wu, d_in[5], DM, FF, 64);
  {
    cuuint64_t dims[5] = {DM, 2, 4, 4, FF / 32};
    cuuint64_t strides[4] = {DM * 2, DM * 16, DM * 4, DM * 64};
    cuuint32_t box[5] = {64, 2, 4, 4, 2};
    cuuint32_t es[5] = {1, 1, 1, 1, 1};
    fn(&p.wd, CU_TENSOR_MAP_DATA_TYPE_BFLOAT16, 5, d_in[6], dims, strides, box, es, CU_TENSOR_MAP_INTERLEAVE_NONE,
       CU_TENSOR_MAP_SWIZZLE_128B, CU_TENSOR_MAP_L2_PROMOTION_L2_256B, CU_TENSOR_MAP_FLOAT_OOB_FILL_NONE);
  }
  p.out = (__nv_bfloat16*)d_out;
  cudaFuncSetAttribute(fused_kernel<true>, cudaFuncAttributeMaxDynamicSharedMemorySize, SMEM_BYTES);
  cudaFuncSetAttribute(fused_kernel<false>, cudaFuncAttributeMaxDynamicSharedMemorySize, SMEM_BYTES);
  bool by_sm;
  {
    int dev = 0, sms = 0, nclusters = 0;
    cudaGetDevice(&dev);
    cudaDeviceGetAttribute(&sms, cudaDevAttrMultiProcessorCount, dev);
    cudaLaunchConfig_t cfg = {};
    cfg.gridDim = dim3(NCTA + NSPARE);
    cfg.blockDim = dim3(384);
    cfg.dynamicSmemBytes = SMEM_BYTES;
    cudaOccupancyMaxActiveClusters(&nclusters, fused_kernel<true>, &cfg);
    by_sm = sms == 132 && nclusters == 66;
  }
  if (by_sm) fused_kernel<true><<<NCTA + NSPARE, 384, SMEM_BYTES, cudaStreamPerThread>>>(p);
  else fused_kernel<false><<<NCTA + NSPARE, 384, SMEM_BYTES, cudaStreamPerThread>>>(p);
}
```

```cpp
#include <cuda_runtime.h>
#include <cuda_bf16.h>
#include <cuda.h>
#include <stdint.h>

namespace {

constexpr int SEQ = 2048, DM = 1024, FF = 3584;
constexpr int NCTA = 128;
constexpr uint32_t CAP = 196608;
constexpr uint32_t KV_OFF = 163840;
constexpr uint32_t KV_WG = 14848;
constexpr uint32_t KV_K = 9216, KV_R = 14336;
constexpr uint32_t STG_OFF = CAP;
constexpr uint32_t MISC_OFF = CAP + 32768;
constexpr uint32_t CSQ_OFF = MISC_OFF + 384;
constexpr uint32_t CSG_OFF = CSQ_OFF + 1536;
constexpr uint32_t SMEM_BYTES = CSG_OFF + 512 + 16;
constexpr int NSPARE = 4;

constexpr uint32_t B_EMPTY = 0, B_FULL = 64, B_DONE = 128  , B_HGO = 144  , B_HALO = 160  , B_CSQ = 176  ,
                   B_CS = 192, B_CSFREE = 200, B_XL = 216, B_BOX1 = 224, M_TAG = CSG_OFF + 512 - MISC_OFF,
                   B_SLAB = 256  , B_SFULL = 256, B_SEMPTY = 320;

enum { F_NONE = 0, F_O0, F_O1, F_X1, F_X1B, F_H0, F_H1, F_X0, F_X0B, F_COUNT };
constexpr int NCS = 3 * DM + 2 * FF;

struct Scratch {
  uint4 flags[16 * 8];
  uint32_t epoch[256];
  float2 stats[8 * SEQ];
  uint4 part[8 * NCS / 4];
  uint4 halo[4 * 16 * 8 * 2 * 5 * 32];
  __nv_bfloat16 x[SEQ * DM], o[SEQ * DM], h[SEQ * FF];
};
__device__ __align__(1024) Scratch g_s;

constexpr int NSEG = 23, NST = 168;
struct Tabs { uint32_t seg[2 * NSEG + 2], seq[9][8], ring[2 * NST + 2]; };
struct Params {
  Scratch* s;
  __nv_bfloat16* out;
  Tabs t;
  CUtensorMap x0, x, o, h, wqkv, wo, wg, wu, wd;
};

__device__ __forceinline__ uint32_t smem_u32(const void* p) { return (uint32_t)__cvta_generic_to_shared(p); }
__device__ __forceinline__ void mbar_init(uint32_t bar, uint32_t cnt) {
  asm volatile("mbarrier.init.shared::cta.b64 [%0], %1;" ::"r"(bar), "r"(cnt));
}
__device__ __forceinline__ void mbar_expect_tx(uint32_t bar, uint32_t bytes) {
  asm volatile("mbarrier.arrive.expect_tx.shared::cta.b64 _, [%0], %1;" ::"r"(bar), "r"(bytes) : "memory");
}
__device__ __forceinline__ void mbar_arrive(uint32_t bar) {
  asm volatile("mbarrier.arrive.shared::cta.b64 _, [%0];" ::"r"(bar) : "memory");
}
__device__ __forceinline__ bool mbar_try(uint32_t bar, uint32_t parity) {
  uint32_t ok;
  asm volatile("{\n.reg .pred p;\nmbarrier.try_wait.parity.shared::cta.b64 p, [%1], %2;\nselp.u32 %0, 1, 0, p;\n}"
               : "=r"(ok) : "r"(bar), "r"(parity) : "memory");
  return ok;
}
__device__ __forceinline__ void mbar_wait(uint32_t bar, uint32_t parity) {
  uint32_t n = 0;
  while (!mbar_try(bar, parity)) {
    if (++n > (1u << 20)) __trap();
  }
}
__device__ __forceinline__ void mbar_wait_idle(uint32_t bar, uint32_t parity) {
  uint32_t n = 0, ok;
  do {
    asm volatile("{\n.reg .pred p;\nmbarrier.try_wait.parity.shared::cta.b64 p, [%1], %2, %3;\nselp.u32 %0, 1, 0, p;\n}"
                 : "=r"(ok) : "r"(bar), "r"(parity), "n"(20000) : "memory");
    if (++n > (1u << 16)) __trap();
  } while (!ok);
}
__device__ __forceinline__ void tma_load(uint32_t dst, const void* tm, uint32_t bar, int c0, int c1) {
  asm volatile("cp.async.bulk.tensor.2d.shared::cluster.global.mbarrier::complete_tx::bytes [%0], [%1, {%3, %4}], [%2];"
               ::"r"(dst), "l"(tm), "r"(bar), "r"(c0), "r"(c1) : "memory");
}
__device__ __forceinline__ void tma_load3(uint32_t dst, const void* tm, uint32_t bar, int c0, int c1) {
  asm volatile("cp.async.bulk.tensor.3d.shared::cluster.global.mbarrier::complete_tx::bytes [%0], [%1, {%3, %4, %5}], [%2];"
               ::"r"(dst), "l"(tm), "r"(bar), "r"(c0), "r"(c1), "r"(0) : "memory");
}
__device__ __forceinline__ void tma_store3(const void* tm, uint32_t src, int c0, int c1) {
  asm volatile("cp.async.bulk.tensor.3d.global.shared::cta.bulk_group [%0, {%2, %3, %4}], [%1];\n"
               "cp.async.bulk.commit_group;\ncp.async.bulk.wait_group 0;" ::"l"(tm), "r"(src), "r"(c0), "r"(c1), "r"(0) : "memory");
}
__device__ __forceinline__ void tma_load_mc(uint32_t dst, const void* tm, uint32_t bar, int c0, int c1) {
  asm volatile("cp.async.bulk.tensor.2d.shared::cluster.global.mbarrier::complete_tx::bytes.multicast::cluster [%0], [%1, {%3, %4}], [%2], %5;"
               ::"r"(dst), "l"(tm), "r"(bar), "r"(c0), "r"(c1), "h"((uint16_t)3) : "memory");
}
__device__ __forceinline__ void tma_load5_mc(uint32_t dst, const void* tm, uint32_t bar, int c0, int c4) {
  asm volatile("cp.async.bulk.tensor.5d.shared::cluster.global.mbarrier::complete_tx::bytes.multicast::cluster [%0], [%1, {%3, %6, %6, %6, %4}], [%2], %5;"
               ::"r"(dst), "l"(tm), "r"(bar), "r"(c0), "r"(c4), "h"((uint16_t)3), "r"(0) : "memory");
}
__device__ __forceinline__ void fence_proxy_async() { asm volatile("fence.proxy.async.global;" ::: "memory"); }
__device__ __forceinline__ void st_tag(uint4* p, uint32_t a, uint32_t b, uint32_t c, uint32_t tag) {
  asm volatile("{\n.reg .b128 t;\n.reg .b64 lo, hi;\nmov.b64 lo, {%1, %2};\nmov.b64 hi, {%3, %4};\nmov.b128 t, {lo, hi};\n"
               "st.relaxed.gpu.global.b128 [%0], t;\n}" ::"l"(p), "r"(a), "r"(b), "r"(c), "r"(tag) : "memory");
}
__device__ __forceinline__ void st_tag_if(bool on, uint4* p, uint32_t a, uint32_t b, uint32_t c, uint32_t tag) {
  asm volatile("{\n.reg .b128 t;\n.reg .b64 lo, hi;\n.reg .pred p;\nsetp.ne.u32 p, %5, 0;\nmov.b64 lo, {%1, %2};\nmov.b64 hi, {%3, %4};\nmov.b128 t, {lo, hi};\n"
               "@p st.relaxed.gpu.global.b128 [%0], t;\n}" ::"l"(p), "r"(a), "r"(b), "r"(c), "r"(tag), "r"((uint32_t)on) : "memory");
}
__device__ __forceinline__ uint4 ld_tag(const uint4* p) {
  uint4 v;
  asm volatile("{\n.reg .b128 t;\n.reg .b64 lo, hi;\nld.relaxed.gpu.global.b128 t, [%4];\nmov.b128 {lo, hi}, t;\n"
               "mov.b64 {%0, %1}, lo;\nmov.b64 {%2, %3}, hi;\n}" : "=r"(v.x), "=r"(v.y), "=r"(v.z), "=r"(v.w) : "l"(p) : "memory");
  return v;
}
__device__ __forceinline__ float tanh_approx(float x) { float y; asm("tanh.approx.f32 %0, %1;" : "=f"(y) : "f"(x)); return y; }
__device__ __forceinline__ void fence_proxy_async_smem() { asm volatile("fence.proxy.async.shared::cta;" ::: "memory"); }
__device__ __forceinline__ void fence_gpu() { asm volatile("fence.release.gpu;" ::: "memory"); }
__device__ __forceinline__ uint32_t ld_epoch(const Params& p) {
  uint32_t e;
  asm volatile("ld.relaxed.gpu.global.u32 %0, [%1];" : "=r"(e) : "l"(p.s->epoch + blockIdx.x) : "memory");
  return e;
}
__device__ __forceinline__ void st_flags(void* p, uint32_t v) {
  asm volatile("st.relaxed.gpu.global.u16 [%0], %1;" ::"l"(p), "h"((uint16_t)((v & 255) * 257)) : "memory");
}
__device__ __forceinline__ uint32_t ld_flag(const void* p) {
  uint32_t v;
  asm volatile("ld.relaxed.gpu.global.u8 %0, [%1];" : "=r"(v) : "l"(p) : "memory");
  return v;
}
__device__ __forceinline__ void wgmma_fence() { asm volatile("wgmma.fence.sync.aligned;" ::: "memory"); }
__device__ __forceinline__ void wgmma_commit() { asm volatile("wgmma.commit_group.sync.aligned;" ::: "memory"); }
template <int N> __device__ __forceinline__ void wgmma_wait() {
  asm volatile("wgmma.wait_group.sync.aligned %0;" ::"n"(N) : "memory");
}
__device__ __forceinline__ void cluster_arrive() { asm volatile("barrier.cluster.arrive.relaxed;" ::: "memory"); }
__device__ __forceinline__ void cluster_wait() { asm volatile("barrier.cluster.wait;" ::: "memory"); }
__device__ __forceinline__ void bar_sync(int id, int n) { asm volatile("bar.sync %0, %1;" ::"r"(id), "r"(n) : "memory"); }
__device__ __forceinline__ uint32_t pack_bf16(float lo, float hi) {
  uint32_t r;
  asm("cvt.rn.bf16x2.f32 %0, %1, %2;" : "=r"(r) : "f"(hi), "f"(lo));
  return r;
}
__device__ __forceinline__ float bf_lo(uint32_t v) { return __uint_as_float(v << 16); }
__device__ __forceinline__ float bf_hi(uint32_t v) { return __uint_as_float(v & 0xffff0000u); }
__device__ __forceinline__ void stsm4(uint32_t a, uint32_t r0, uint32_t r1, uint32_t r2, uint32_t r3) {
  asm volatile("stmatrix.sync.aligned.m8n8.x4.shared.b16 [%0], {%1, %2, %3, %4};" ::"r"(a), "r"(r0), "r"(r1), "r"(r2), "r"(r3) : "memory");
}
__device__ __forceinline__ void ldsm4(uint32_t a, uint32_t& r0, uint32_t& r1, uint32_t& r2, uint32_t& r3) {
  asm volatile("ldmatrix.sync.aligned.m8n8.x4.shared.b16 {%0, %1, %2, %3}, [%4];" : "=r"(r0), "=r"(r1), "=r"(r2), "=r"(r3) : "r"(a) : "memory");
}
__device__ __forceinline__ void ldsm4t(uint32_t a, uint32_t& r0, uint32_t& r1, uint32_t& r2, uint32_t& r3) {
  asm volatile("ldmatrix.sync.aligned.m8n8.x4.trans.shared.b16 {%0, %1, %2, %3}, [%4];" : "=r"(r0), "=r"(r1), "=r"(r2), "=r"(r3) : "r"(a) : "memory");
}
__device__ __forceinline__ void mma16816(float (&c)[4], uint32_t a0, uint32_t a1, uint32_t a2, uint32_t a3, uint32_t b0, uint32_t b1) {
  asm volatile("mma.sync.aligned.m16n8k16.row.col.f32.bf16.bf16.f32 {%0,%1,%2,%3}, {%4,%5,%6,%7}, {%8,%9}, {%0,%1,%2,%3};"
               : "+f"(c[0]), "+f"(c[1]), "+f"(c[2]), "+f"(c[3]) : "r"(a0), "r"(a1), "r"(a2), "r"(a3), "r"(b0), "r"(b1));
}
__device__ __forceinline__ float ex2(float x) { float y; asm("ex2.approx.ftz.f32 %0, %1;" : "=f"(y) : "f"(x)); return y; }
__device__ __forceinline__ float rcp(float x) { float y; asm("rcp.approx.ftz.f32 %0, %1;" : "=f"(y) : "f"(x)); return y; }
__device__ __forceinline__ uint32_t pin(uint32_t a) {
  uint32_t r;
  asm volatile("mov.u32 %0, %1;" : "=r"(r) : "r"(a) : "memory");
  return r;
}
__device__ __forceinline__ float lds32f(uint32_t a) {
  float v;
  asm volatile("ld.shared.f32 %0, [%1];" : "=f"(v) : "r"(a) : "memory");
  return v;
}
__device__ __forceinline__ void sts32f(uint32_t a, float v) { asm volatile("st.shared.f32 [%0], %1;" ::"r"(a), "f"(v) : "memory"); }
__device__ __forceinline__ void sts64f(uint32_t a, float x, float y) { asm volatile("st.shared.v2.f32 [%0], {%1, %2};" ::"r"(a), "f"(x), "f"(y) : "memory"); }
__device__ __forceinline__ float2 ld_b64(const void* p) {
  float2 v;
  asm volatile("{\n.reg .b64 t;\nld.relaxed.gpu.global.b64 t, [%2];\nmov.b64 {%0, %1}, t;\n}" : "=f"(v.x), "=f"(v.y) : "l"(p) : "memory");
  return v;
}
__device__ __forceinline__ void st_b64(void* p, uint32_t x, uint32_t y) {
  asm volatile("{\n.reg .b64 t;\nmov.b64 t, {%1, %2};\nst.relaxed.gpu.global.b64 [%0], t;\n}" ::"l"(p), "r"(x), "r"(y) : "memory");
}
__device__ __forceinline__ uint4 lds128(uint32_t a) {
  uint4 v;
  asm volatile("ld.shared.v4.u32 {%0, %1, %2, %3}, [%4];" : "=r"(v.x), "=r"(v.y), "=r"(v.z), "=r"(v.w) : "r"(a) : "memory");
  return v;
}
__device__ __forceinline__ float qsum(float v) {
  v += __shfl_xor_sync(0xffffffffu, v, 1);
  v += __shfl_xor_sync(0xffffffffu, v, 2);
  return v;
}
__device__ __forceinline__ void sts128(uint32_t a, uint32_t x, uint32_t y, uint32_t z, uint32_t w) {
  asm volatile("st.shared.v4.u32 [%0], {%1, %2, %3, %4};" ::"r"(a), "r"(x), "r"(y), "r"(z), "r"(w) : "memory");
}
__device__ __forceinline__ float4 lds128f(uint32_t a) {
  float4 v;
  asm volatile("ld.shared.v4.f32 {%0, %1, %2, %3}, [%4];" : "=f"(v.x), "=f"(v.y), "=f"(v.z), "=f"(v.w) : "r"(a) : "memory");
  return v;
}
__device__ __forceinline__ void stg128(void* p, uint32_t x, uint32_t y, uint32_t z, uint32_t w) {
  asm volatile("st.global.v4.u32 [%0], {%1, %2, %3, %4};" ::"l"(p), "r"(x), "r"(y), "r"(z), "r"(w) : "memory");
}
__device__ __forceinline__ void mma1688z(float (&c)[4], uint32_t a0, uint32_t b0) {
  asm volatile("mma.sync.aligned.m16n8k8.row.col.f32.bf16.bf16.f32 {%0,%1,%2,%3}, {%4,%5}, {%6}, {%7,%7,%7,%7};"
               : "=f"(c[0]), "=f"(c[1]), "=f"(c[2]), "=f"(c[3]) : "r"(a0), "r"(0u), "r"(b0), "f"(0.f));
}
__device__ __forceinline__ void mma16816z(float (&c)[4], uint32_t a0, uint32_t a1, uint32_t a2, uint32_t a3, uint32_t b0, uint32_t b1) {
  asm volatile("mma.sync.aligned.m16n8k16.row.col.f32.bf16.bf16.f32 {%0,%1,%2,%3}, {%4,%5,%6,%7}, {%8,%9}, {%10,%10,%10,%10};"
               : "=f"(c[0]), "=f"(c[1]), "=f"(c[2]), "=f"(c[3]) : "r"(a0), "r"(a1), "r"(a2), "r"(a3), "r"(b0), "r"(b1), "f"(0.f));
}

__device__ __forceinline__ void wgmma_n128(float (&d0)[64], uint64_t da, uint64_t db) {
  asm volatile(
    "wgmma.mma_async.sync.aligned.m64n128k16.f32.bf16.bf16 "
    "{%0,%1,%2,%3,%4,%5,%6,%7,%8,%9,%10,%11,%12,%13,%14,%15,"
    "%16,%17,%18,%19,%20,%21,%22,%23,%24,%25,%26,%27,%28,%29,%30,%31,"
    "%32,%33,%34,%35,%36,%37,%38,%39,%40,%41,%42,%43,%44,%45,%46,%47,"
    "%48,%49,%50,%51,%52,%53,%54,%55,%56,%57,%58,%59,%60,%61,%62,%63},"
    " %64, %65, 1, 1, 1, 0, 1;"
    : "+f"(d0[0]), "+f"(d0[1]), "+f"(d0[2]), "+f"(d0[3]), "+f"(d0[4]), "+f"(d0[5]), "+f"(d0[6]), "+f"(d0[7]),
      "+f"(d0[8]), "+f"(d0[9]), "+f"(d0[10]), "+f"(d0[11]), "+f"(d0[12]), "+f"(d0[13]), "+f"(d0[14]), "+f"(d0[15]),
      "+f"(d0[16]), "+f"(d0[17]), "+f"(d0[18]), "+f"(d0[19]), "+f"(d0[20]), "+f"(d0[21]), "+f"(d0[22]), "+f"(d0[23]),
      "+f"(d0[24]), "+f"(d0[25]), "+f"(d0[26]), "+f"(d0[27]), "+f"(d0[28]), "+f"(d0[29]), "+f"(d0[30]), "+f"(d0[31]),
      "+f"(d0[32]), "+f"(d0[33]), "+f"(d0[34]), "+f"(d0[35]), "+f"(d0[36]), "+f"(d0[37]), "+f"(d0[38]), "+f"(d0[39]),
      "+f"(d0[40]), "+f"(d0[41]), "+f"(d0[42]), "+f"(d0[43]), "+f"(d0[44]), "+f"(d0[45]), "+f"(d0[46]), "+f"(d0[47]),
      "+f"(d0[48]), "+f"(d0[49]), "+f"(d0[50]), "+f"(d0[51]), "+f"(d0[52]), "+f"(d0[53]), "+f"(d0[54]), "+f"(d0[55]),
      "+f"(d0[56]), "+f"(d0[57]), "+f"(d0[58]), "+f"(d0[59]), "+f"(d0[60]), "+f"(d0[61]), "+f"(d0[62]), "+f"(d0[63])
    : "l"(da), "l"(db));
}
__device__ __forceinline__ void wgmma_n128_init(float (&d0)[64], uint64_t da, uint64_t db) {
  asm volatile(
    "wgmma.mma_async.sync.aligned.m64n128k16.f32.bf16.bf16 "
    "{%0,%1,%2,%3,%4,%5,%6,%7,%8,%9,%10,%11,%12,%13,%14,%15,"
    "%16,%17,%18,%19,%20,%21,%22,%23,%24,%25,%26,%27,%28,%29,%30,%31,"
    "%32,%33,%34,%35,%36,%37,%38,%39,%40,%41,%42,%43,%44,%45,%46,%47,"
    "%48,%49,%50,%51,%52,%53,%54,%55,%56,%57,%58,%59,%60,%61,%62,%63},"
    " %64, %65, 0, 1, 1, 0, 1;"
    : "=f"(d0[0]), "=f"(d0[1]), "=f"(d0[2]), "=f"(d0[3]), "=f"(d0[4]), "=f"(d0[5]), "=f"(d0[6]), "=f"(d0[7]),
      "=f"(d0[8]), "=f"(d0[9]), "=f"(d0[10]), "=f"(d0[11]), "=f"(d0[12]), "=f"(d0[13]), "=f"(d0[14]), "=f"(d0[15]),
      "=f"(d0[16]), "=f"(d0[17]), "=f"(d0[18]), "=f"(d0[19]), "=f"(d0[20]), "=f"(d0[21]), "=f"(d0[22]), "=f"(d0[23]),
      "=f"(d0[24]), "=f"(d0[25]), "=f"(d0[26]), "=f"(d0[27]), "=f"(d0[28]), "=f"(d0[29]), "=f"(d0[30]), "=f"(d0[31]),
      "=f"(d0[32]), "=f"(d0[33]), "=f"(d0[34]), "=f"(d0[35]), "=f"(d0[36]), "=f"(d0[37]), "=f"(d0[38]), "=f"(d0[39]),
      "=f"(d0[40]), "=f"(d0[41]), "=f"(d0[42]), "=f"(d0[43]), "=f"(d0[44]), "=f"(d0[45]), "=f"(d0[46]), "=f"(d0[47]),
      "=f"(d0[48]), "=f"(d0[49]), "=f"(d0[50]), "=f"(d0[51]), "=f"(d0[52]), "=f"(d0[53]), "=f"(d0[54]), "=f"(d0[55]),
      "=f"(d0[56]), "=f"(d0[57]), "=f"(d0[58]), "=f"(d0[59]), "=f"(d0[60]), "=f"(d0[61]), "=f"(d0[62]), "=f"(d0[63])
    : "l"(da), "l"(db));
}
__device__ __forceinline__ void wgmma_n192(float (&d0)[96], uint64_t da, uint64_t db) {
  asm volatile(
    "wgmma.mma_async.sync.aligned.m64n192k16.f32.bf16.bf16 "
    "{%0,%1,%2,%3,%4,%5,%6,%7,%8,%9,%10,%11,%12,%13,%14,%15,"
    "%16,%17,%18,%19,%20,%21,%22,%23,%24,%25,%26,%27,%28,%29,%30,%31,"
    "%32,%33,%34,%35,%36,%37,%38,%39,%40,%41,%42,%43,%44,%45,%46,%47,"
    "%48,%49,%50,%51,%52,%53,%54,%55,%56,%57,%58,%59,%60,%61,%62,%63,"
    "%64,%65,%66,%67,%68,%69,%70,%71,%72,%73,%74,%75,%76,%77,%78,%79,"
    "%80,%81,%82,%83,%84,%85,%86,%87,%88,%89,%90,%91,%92,%93,%94,%95},"
    " %96, %97, 1, 1, 1, 0, 1;"
    : "+f"(d0[0]), "+f"(d0[1]), "+f"(d0[2]), "+f"(d0[3]), "+f"(d0[4]), "+f"(d0[5]), "+f"(d0[6]), "+f"(d0[7]),
      "+f"(d0[8]), "+f"(d0[9]), "+f"(d0[10]), "+f"(d0[11]), "+f"(d0[12]), "+f"(d0[13]), "+f"(d0[14]), "+f"(d0[15]),
      "+f"(d0[16]), "+f"(d0[17]), "+f"(d0[18]), "+f"(d0[19]), "+f"(d0[20]), "+f"(d0[21]), "+f"(d0[22]), "+f"(d0[23]),
      "+f"(d0[24]), "+f"(d0[25]), "+f"(d0[26]), "+f"(d0[27]), "+f"(d0[28]), "+f"(d0[29]), "+f"(d0[30]), "+f"(d0[31]),
      "+f"(d0[32]), "+f"(d0[33]), "+f"(d0[34]), "+f"(d0[35]), "+f"(d0[36]), "+f"(d0[37]), "+f"(d0[38]), "+f"(d0[39]),
      "+f"(d0[40]), "+f"(d0[41]), "+f"(d0[42]), "+f"(d0[43]), "+f"(d0[44]), "+f"(d0[45]), "+f"(d0[46]), "+f"(d0[47]),
      "+f"(d0[48]), "+f"(d0[49]), "+f"(d0[50]), "+f"(d0[51]), "+f"(d0[52]), "+f"(d0[53]), "+f"(d0[54]), "+f"(d0[55]),
      "+f"(d0[56]), "+f"(d0[57]), "+f"(d0[58]), "+f"(d0[59]), "+f"(d0[60]), "+f"(d0[61]), "+f"(d0[62]), "+f"(d0[63]),
      "+f"(d0[64]), "+f"(d0[65]), "+f"(d0[66]), "+f"(d0[67]), "+f"(d0[68]), "+f"(d0[69]), "+f"(d0[70]), "+f"(d0[71]),
      "+f"(d0[72]), "+f"(d0[73]), "+f"(d0[74]), "+f"(d0[75]), "+f"(d0[76]), "+f"(d0[77]), "+f"(d0[78]), "+f"(d0[79]),
      "+f"(d0[80]), "+f"(d0[81]), "+f"(d0[82]), "+f"(d0[83]), "+f"(d0[84]), "+f"(d0[85]), "+f"(d0[86]), "+f"(d0[87]),
      "+f"(d0[88]), "+f"(d0[89]), "+f"(d0[90]), "+f"(d0[91]), "+f"(d0[92]), "+f"(d0[93]), "+f"(d0[94]), "+f"(d0[95])
    : "l"(da), "l"(db));
}
__device__ __forceinline__ void wgmma_n192_init(float (&d0)[96], uint64_t da, uint64_t db) {
  asm volatile(
    "wgmma.mma_async.sync.aligned.m64n192k16.f32.bf16.bf16 "
    "{%0,%1,%2,%3,%4,%5,%6,%7,%8,%9,%10,%11,%12,%13,%14,%15,"
    "%16,%17,%18,%19,%20,%21,%22,%23,%24,%25,%26,%27,%28,%29,%30,%31,"
    "%32,%33,%34,%35,%36,%37,%38,%39,%40,%41,%42,%43,%44,%45,%46,%47,"
    "%48,%49,%50,%51,%52,%53,%54,%55,%56,%57,%58,%59,%60,%61,%62,%63,"
    "%64,%65,%66,%67,%68,%69,%70,%71,%72,%73,%74,%75,%76,%77,%78,%79,"
    "%80,%81,%82,%83,%84,%85,%86,%87,%88,%89,%90,%91,%92,%93,%94,%95},"
    " %96, %97, 0, 1, 1, 0, 1;"
    : "=f"(d0[0]), "=f"(d0[1]), "=f"(d0[2]), "=f"(d0[3]), "=f"(d0[4]), "=f"(d0[5]), "=f"(d0[6]), "=f"(d0[7]),
      "=f"(d0[8]), "=f"(d0[9]), "=f"(d0[10]), "=f"(d0[11]), "=f"(d0[12]), "=f"(d0[13]), "=f"(d0[14]), "=f"(d0[15]),
      "=f"(d0[16]), "=f"(d0[17]), "=f"(d0[18]), "=f"(d0[19]), "=f"(d0[20]), "=f"(d0[21]), "=f"(d0[22]), "=f"(d0[23]),
      "=f"(d0[24]), "=f"(d0[25]), "=f"(d0[26]), "=f"(d0[27]), "=f"(d0[28]), "=f"(d0[29]), "=f"(d0[30]), "=f"(d0[31]),
      "=f"(d0[32]), "=f"(d0[33]), "=f"(d0[34]), "=f"(d0[35]), "=f"(d0[36]), "=f"(d0[37]), "=f"(d0[38]), "=f"(d0[39]),
      "=f"(d0[40]), "=f"(d0[41]), "=f"(d0[42]), "=f"(d0[43]), "=f"(d0[44]), "=f"(d0[45]), "=f"(d0[46]), "=f"(d0[47]),
      "=f"(d0[48]), "=f"(d0[49]), "=f"(d0[50]), "=f"(d0[51]), "=f"(d0[52]), "=f"(d0[53]), "=f"(d0[54]), "=f"(d0[55]),
      "=f"(d0[56]), "=f"(d0[57]), "=f"(d0[58]), "=f"(d0[59]), "=f"(d0[60]), "=f"(d0[61]), "=f"(d0[62]), "=f"(d0[63]),
      "=f"(d0[64]), "=f"(d0[65]), "=f"(d0[66]), "=f"(d0[67]), "=f"(d0[68]), "=f"(d0[69]), "=f"(d0[70]), "=f"(d0[71]),
      "=f"(d0[72]), "=f"(d0[73]), "=f"(d0[74]), "=f"(d0[75]), "=f"(d0[76]), "=f"(d0[77]), "=f"(d0[78]), "=f"(d0[79]),
      "=f"(d0[80]), "=f"(d0[81]), "=f"(d0[82]), "=f"(d0[83]), "=f"(d0[84]), "=f"(d0[85]), "=f"(d0[86]), "=f"(d0[87]),
      "=f"(d0[88]), "=f"(d0[89]), "=f"(d0[90]), "=f"(d0[91]), "=f"(d0[92]), "=f"(d0[93]), "=f"(d0[94]), "=f"(d0[95])
    : "l"(da), "l"(db));
}
enum { A_LOC = 0, A_X = 1, A_O = 2, A_H = 3 };
enum { W_QKV = 0, W_O = 1, W_G = 2, W_D = 3 };
enum { K_L = 0, K_E7 = 1, K_O7 = 2, K_OL = 3, K_OR = 4, K_LIN = 5 };
struct Seg { int nb, n, a, w, c0, c1, ks, dep; };
constexpr int NOA = 2;
constexpr Seg SEGS[NSEG] = {
  {3, 2, A_LOC, W_QKV, 1, 0, K_L, F_NONE},
  {3, 2, A_LOC, W_QKV, 0, 0, K_L, F_NONE},
  {3, 7, A_X, W_QKV, 0, 0, K_E7, F_X0},
  {3, 7, A_X, W_QKV, 0, 0, K_O7, F_X0B},
  {3, 7, A_X, W_QKV, 1, 0, K_E7, F_NONE},
  {3, 7, A_X, W_QKV, 1, 0, K_O7, F_NONE},
  {2, 8, A_O, W_O, 0, 0, K_LIN, F_O0},
  {2, 1, A_LOC, W_O, 0, 0, K_OL, F_NONE},
  {2, 7, A_O, W_O, 0, 0, K_OR, F_O1},
  {2, 2, A_LOC, W_G, 2, 0, K_L, F_NONE},
  {4, 2, A_LOC, W_G, 0, 1, K_L, F_NONE},
  {4, 7, A_X, W_G, 0, 1, K_E7, F_X1},
  {2, 7, A_X, W_G, 0, 0, K_O7, F_X1B},
  {4, 7, A_X, W_G, 2, 1, K_O7, F_NONE},
  {4, 7, A_X, W_G, 2, 3, K_E7, F_NONE},
  {4, 2, A_LOC, W_G, 4, 3, K_L, F_NONE},
  {4, 7, A_X, W_G, 4, 3, K_O7, F_NONE},
  {4, 7, A_X, W_G, 4, 5, K_E7, F_NONE},
  {4, 2, A_LOC, W_G, 6, 5, K_L, F_NONE},
  {4, 7, A_X, W_G, 6, 5, K_O7, F_NONE},
  {2, 7, A_X, W_G, 6, 0, K_E7, F_NONE},
  {2, 32, A_H, W_D, 0, 0, K_LIN, F_H0},
  {2, 24, A_H, W_D, 4, 0, K_LIN, F_H1},
};
constexpr Tabs make_tabs() {
  Tabs t{};
  int pa[2 * NST] = {}, pb[2 * NST] = {}, sa[2 * NST] = {}, sb[2 * NST] = {};
  int pos = 12, it = 0;
  constexpr int o0 = 32;
  for (int sg = 0; sg < 2 * NSEG; sg++) {
    Seg g = SEGS[sg % NSEG];
    if (sg < 6) { g.a = A_X; g.dep = F_NONE; }
    for (int k = 0; k < g.n; k++, it++) {
      const int cap = it % NST < o0 + 3 ? 20 : 24;
      const int a = (g.a == A_LOC && g.n > 1 && g.c0 < 4) ? 0 : 2, b = g.nb, rem = cap - pos;
      sa[it] = g.a == A_LOC ? 0 : 2; sb[it] = b;
      if (rem >= a + b) { pa[it] = pos; pb[it] = pos + a; pos += a + b; }
      else if (a && rem == a) { pa[it] = pos; pb[it] = 0; pos = b; }
      else if (a && rem == b) { pb[it] = pos; pa[it] = 0; pos = a; }
      else { pa[it] = 0; pb[it] = a; pos = a + b; }
      if (g.a == A_LOC) pa[it] = 24 + 2 * k;
    }
    t.seg[sg] = (uint32_t)(g.n | g.nb << 6 | g.a << 9 | g.w << 11 | g.c0 << 13 | g.c1 << 16 | g.ks << 19 | g.dep << 22);
  }
  for (int i = 0; i < 2 * NST; i++) {
    int lag[2] = {8, 8};
    const int p[2] = {pa[i], pb[i]}, n[2] = {sa[i], sb[i]}, io = i % NST - o0;
    for (int x = 0; x < 2; x++) {
      for (int l = i < 8 ? i : 8; l >= 1; l--) {
        const int q[2] = {pa[i - l], pb[i - l]}, m[2] = {sa[i - l], sb[i - l]};
        for (int y = 0; y < 2; y++)
          if (n[x] && m[y] && p[x] < q[y] + m[y] && q[y] < p[x] + n[x]) lag[x] = l;
      }
      if (io > 0 && io < 8 && p[x] >= 20 && io - NOA < lag[x]) lag[x] = io - NOA;
    }
    if (i == NST + 3) lag[1] = 6;
    if (i < o0 && lag[0] < lag[1]) lag[1] = lag[0];
    t.ring[i] = (uint32_t)(pa[i] * 512 | lag[1] | lag[0] << 4 | pb[i] * 512 << 16);
  }
  int waits[2 * NST] = {};
  for (int i = 0; i < 2 * NST; i++)
    for (int x = 0; x < 2; x++) {
      const int j = i - (int)((t.ring[i] >> (4 * x)) & 15);
      if (j >= 0 && (!x || (i >= o0 && sa[i]))) waits[j]++;
    }
  for (int j = 0; j < 2 * NST - 8; j++)
    for (int x = 1; x >= 0; x--)
      for (int i = j + 7; i > j && !waits[j]; i--) {
        const int q = i - (int)((t.ring[i] >> (4 * x)) & 15);
        if (q < j && waits[q] > 1 && (!x || sa[i])) { waits[q]--; waits[j]++; t.ring[i] -= (uint32_t)(j - q) << (4 * x); }
      }
  for (int jc = 0; jc < 8; jc++)
    for (int ks = 0; ks < K_LIN; ks++)
      for (int i = 0; i < 8; i++) {
        const int u = i == jc ? 7 : i;
        t.seq[jc][ks] |= (uint32_t)(ks == K_L ? jc * 2 + (i & 1) : ks == K_OL ? 8 + jc : ks == K_OR ? 8 + u : u * 2 + (ks != K_E7)) << (4 * i);
      }
  t.seq[8][K_L] = 0x10; t.seq[8][K_E7] = 0x8765432; t.seq[8][K_O7] = 0xfedcba9;
  return t;
}

constexpr uint32_t RING0 = make_tabs().ring[0];

__device__ __forceinline__ bool elect_one() {
  uint32_t pred;
  asm volatile("{\n.reg .pred p;\nelect.sync _|p, 0xffffffff;\nselp.u32 %0, 1, 0, p;\n}" : "=r"(pred));
  return pred;
}

struct Ctx {
  const Params& p;
  uint32_t sb;
  uint32_t it;
  uint32_t lp;
  uint32_t ebar;
  bool rel;
  uint32_t da, db;
  int w, wg, wi, lane;
  int rb, jc;
  float m0, r0, m1, r1;
};
struct Stage { uint64_t da, db; };
struct Stats { float2 a, b, c, d; };

__device__ __forceinline__ uint32_t ld_tag_s(uint32_t sb) { return __float_as_uint(lds32f(sb + MISC_OFF + M_TAG)); }
__device__ __forceinline__ void carrive(const Ctx& c, uint32_t bar) {
  __syncwarp();
  if (c.lane == 0) mbar_arrive(c.sb + MISC_OFF + bar);
}

__device__ __forceinline__ Stage peek(const Ctx& c) {
  const uint32_t e = c.p.t.ring[c.it];
  Stage s;
  asm("mov.b64 %0, {%1, 0x40000040};" : "=l"(s.da) : "r"(c.da + (e & 0x3e00)));
  asm("mov.b64 %0, {%1, 0x40000040};" : "=l"(s.db) : "r"(c.db + (e >> 16)));
  return s;
}
__device__ __forceinline__ void wait_full(Ctx& c) {
  mbar_wait(c.sb + MISC_OFF + B_FULL + (c.it & 7) * 8, (c.it >> 3) & 1);
  c.it++;
}
__device__ __forceinline__ void release(Ctx& c) {
  if (c.rel) asm volatile("mbarrier.arrive.shared::cluster.b64 _, [%0];" ::"r"(c.ebar) : "memory");
  c.ebar = (c.ebar + 8) & ~64u;
}
__device__ __forceinline__ void load_stats(const Ctx& c, Stats& s) {
  const int lane = pin(c.lane);
  const float2* sp = c.p.s->stats + (lane & 3) * 2 * SEQ + pin(c.rb) * 128 + pin(c.w) * 16 + (lane >> 2);
  s.a = ld_b64(sp); s.b = ld_b64(sp + SEQ); s.c = ld_b64(sp + 8); s.d = ld_b64(sp + SEQ + 8);
}
__device__ __forceinline__ void combine2(float2 a, float2 b, float& mean, float& rstd) {
  mean = qsum(a.x + b.x) * 0.125f;
  const float d0 = a.x - mean, d1 = b.x - mean;
  const float m2 = qsum(a.y + b.y + 128.f * (d0 * d0 + d1 * d1));
  rstd = rsqrtf(m2 * (1.f / 1024.f) + 1e-5f);
}
__device__ __forceinline__ void combine_stats(Ctx& c, Stats& s, uint32_t tag) {
  uint32_t n = 0;
  while (true) {
    const uint32_t x = tag & 1, y = tag >> 1;
    const uint32_t bad = (__float_as_uint(s.a.x) ^ x) | (__float_as_uint(s.b.x) ^ x) | (__float_as_uint(s.c.x) ^ x) | (__float_as_uint(s.d.x) ^ x) |
                         (__float_as_uint(s.a.y) ^ y) | (__float_as_uint(s.b.y) ^ y) | (__float_as_uint(s.c.y) ^ y) | (__float_as_uint(s.d.y) ^ y);
    if (__all_sync(0xffffffffu, !(bad & 1))) break;
    if (++n > (1u << 18)) __trap();
    load_stats(c, s);
  }
  combine2(s.a, s.b, c.m0, c.r0);
  combine2(s.c, s.d, c.m1, c.r1);
}

template <bool INIT> __device__ __forceinline__ void mm(float (&A)[64], uint64_t da, uint64_t db) {
  if (INIT) wgmma_n128_init(A, da, db); else wgmma_n128(A, da, db);
}
template <bool INIT> __device__ __forceinline__ void mm(float (&A)[96], uint64_t da, uint64_t db) {
  if (INIT) wgmma_n192_init(A, da, db); else wgmma_n192(A, da, db);
}
__device__ __forceinline__ void keep(float& v) { asm volatile("" : "+f"(v)); }
__device__ __forceinline__ void keep(uint32_t& v) { asm volatile("" : "+r"(v)); }
template <int N> __device__ __forceinline__ void keep_all(float (&A)[N]) {
#pragma unroll
  for (int i = 0; i < N; i++) keep(A[i]);
}
__device__ __forceinline__ void cut(const Stage& s) {
  asm volatile("{\n.reg .pred p;\nsetp.eq.u32 p, %0, 0xffffffff;\n@p trap;\n}" ::"r"((uint32_t)s.db) : "memory");
}
struct Nop { __device__ __forceinline__ void operator()() const {} };
template <bool INIT, bool FIRST, int WAIT = 1, int N, class HOOK>
__device__ __forceinline__ void step1(Ctx& c, Stage& s, float (&A)[N], HOOK&& hook) {
  wait_full(c);
  wgmma_fence();
  mm<INIT>(A, s.da, s.db);
  if (!FIRST) {
    wgmma_commit();
    wgmma_wait<1>();
    release(c);
  }
  mm<false>(A, s.da + 2, s.db + 128);
  mm<false>(A, s.da + 4, s.db + 256);
  wgmma_commit();
  mm<false>(A, s.da + 6, s.db + 384);
  wgmma_commit();
  s = peek(c);
  if (sizeof(hook) > 1) cut(s);
  hook();
  if (WAIT == 2 || (WAIT == 1 && sizeof(hook) == 1)) wgmma_wait<1>();
}
template <bool INIT, int WAIT = 1, class HOOK>
__device__ __forceinline__ void step2(Ctx& c, Stage& s, float (&A)[64], float (&B)[64], HOOK&& hook) {
  wait_full(c);
  wgmma_fence();
  mm<INIT>(A, s.da, s.db);
  mm<INIT>(B, s.da, s.db + 1024);
  wgmma_commit();
  wgmma_wait<1>();
  release(c);
  mm<false>(A, s.da + 2, s.db + 128);
  mm<false>(B, s.da + 2, s.db + 1152);
  mm<false>(A, s.da + 4, s.db + 256);
  mm<false>(B, s.da + 4, s.db + 1280);
  wgmma_commit();
  mm<false>(A, s.da + 6, s.db + 384);
  mm<false>(B, s.da + 6, s.db + 1408);
  wgmma_commit();
  s = peek(c);
  if (sizeof(hook) > 1) cut(s);
  hook();
  if (WAIT == 2 || (WAIT == 1 && sizeof(hook) == 1)) wgmma_wait<1>();
}
template <bool INIT>
__device__ __forceinline__ void stage128(float (&A)[64], uint64_t da, uint64_t db) {
  mm<INIT>(A, da, db);
  mm<false>(A, da + 2, db + 128);
  mm<false>(A, da + 4, db + 256);
  mm<false>(A, da + 6, db + 384);
}

__device__ __forceinline__ uint32_t warp_rows(const Ctx& c) { return c.sb + STG_OFF + pin(c.w) * 2048; }
__device__ __forceinline__ uint32_t stg_base(uint32_t rows, int lane) {
  return rows + (lane & 15) * 128 + (((lane >> 4) ^ (lane & 7)) << 4);
}
__device__ __forceinline__ int seq_row(const Ctx& c, int r) {
  const int w = pin(c.w);
  return pin(c.rb) * 128 + (w & 3) * 32 + (w >> 2) + 2 * r;
}
template <int H>
__device__ __forceinline__ void resid_init(const Ctx& c, float (&A)[64]) {
  const uint32_t sta = stg_base(warp_rows(c), pin(c.lane)) + H * 16384;
#pragma unroll
  for (int b = 0; b < 8; b += 2) {
    uint32_t v0, v1, v2, v3;
    ldsm4(sta ^ (b << 4), v0, v1, v2, v3);
    float* a = A + H * 32 + 4 * b;
    a[0] = bf_lo(v0); a[1] = bf_hi(v0); a[2] = bf_lo(v1); a[3] = bf_hi(v1);
    a[4] = bf_lo(v2); a[5] = bf_hi(v2); a[6] = bf_lo(v3); a[7] = bf_hi(v3);
  }
#pragma unroll
  for (int i = 0; i < 32; i++) keep(A[H * 32 + i]);
}
__device__ __forceinline__ void stats_acc(const Ctx& c, int h, Stats& t) {
  const uint32_t sta = (stg_base(warp_rows(c), pin(c.lane)) ^ ((h & 1) << 6)) + (h >> 1) * 16384;
  uint32_t v[8];
#pragma unroll
  for (int b = 0; b < 2; b++) ldsm4(sta ^ (b << 5), v[4 * b], v[4 * b + 1], v[4 * b + 2], v[4 * b + 3]);
#pragma unroll
  for (int i = 0; i < 8; i += 2) {
    const float a = bf_lo(v[i]), b = bf_hi(v[i]), d = bf_lo(v[i + 1]), e = bf_hi(v[i + 1]);
    t.a.x += a + b; t.b.x = fmaf(a, a, fmaf(b, b, t.b.x));
    t.a.y += d + e; t.b.y = fmaf(d, d, fmaf(e, e, t.b.y));
  }
}
__device__ __forceinline__ void stats_store(const Ctx& c, const Stats& t, uint32_t tag) {
  const int lane = pin(c.lane), rh = lane & 1;
  float sum = (rh ? t.a.y : t.a.x) + __shfl_xor_sync(0xffffffffu, rh ? t.a.x : t.a.y, 1);
  float sq = (rh ? t.b.y : t.b.x) + __shfl_xor_sync(0xffffffffu, rh ? t.b.x : t.b.y, 1);
  sum += __shfl_xor_sync(0xffffffffu, sum, 2);
  sq += __shfl_xor_sync(0xffffffffu, sq, 2);
  const float mu = sum * (1.f / 128.f), m2 = fmaxf(fmaf(-mu, sum, sq), 0.f);
  if (!(lane & 2))
    st_b64(c.p.s->stats + pin(c.jc) * SEQ + pin(c.rb) * 128 + pin(c.w) * 16 + (lane >> 2) + rh * 8,
           (__float_as_uint(mu) & ~1u) | (tag & 1), (__float_as_uint(m2) & ~1u) | (tag >> 1));
}
__device__ __forceinline__ void store_box(const Ctx& c, __nv_bfloat16* g, int h) {
  const int lane = pin(c.lane), r = lane >> 3, ch = lane & 7;
  const uint32_t rows = warp_rows(c) + r * 128 + h * 16384;
  g += (size_t)seq_row(c, r) * DM + pin(c.jc) * 128 + h * 64 + ch * 8;
  uint4 v[4];
#pragma unroll
  for (int i = 0; i < 4; i++) v[i] = lds128(rows + i * 512 + ((ch ^ ((r + 4 * i) & 7)) << 4));
#pragma unroll
  for (int i = 0; i < 4; i++) stg128(g + i * 8 * DM, v[i].x, v[i].y, v[i].z, v[i].w);
}
template <int H>
__device__ __forceinline__ void stage_box(uint32_t sta, const float (&A)[64]) {
#pragma unroll
  for (int b = 8 * H; b < 8 * H + 8; b += 2)
    stsm4((sta ^ ((b & 7) << 4)) + H * 16384, pack_bf16(A[4 * b], A[4 * b + 1]), pack_bf16(A[4 * b + 2], A[4 * b + 3]),
          pack_bf16(A[4 * b + 4], A[4 * b + 5]), pack_bf16(A[4 * b + 6], A[4 * b + 7]));
}
__device__ __forceinline__ void finish_x(Ctx& c, float (&A)[64], __nv_bfloat16* g) {
  const uint32_t sta = stg_base(warp_rows(c), pin(c.lane));
  wgmma_wait<0>();
  release(c);
  if (c.it == 2 * NST) cluster_arrive();
  keep_all(A);
  stage_box<0>(sta, A);
  __syncwarp();
  store_box(c, g, 0);
  carrive(c, B_DONE + c.wg * 8);
  stage_box<1>(sta, A);
  fence_proxy_async_smem();
  carrive(c, B_BOX1);
  bar_sync(2 + c.wg, 128);
}

struct Att { uint32_t q[16], k[16], kp[8], p[2][4], vp[8], vf[16]; float s[2][3][4], v[4][2], o[8][4]; };
struct Cs { float4 v[4]; };
__device__ __forceinline__ uint32_t vswz(int r) { return ((r & 1) << 2) | ((r >> 1) & 3); }
__device__ __forceinline__ uint32_t kv_base(const Ctx& c) { return c.sb + KV_OFF + (pin(c.w) >> 2) * KV_WG; }
__device__ __forceinline__ uint4* halo_ptr(const Params& p, int lp, int s, int rb, int jc, int wg, int lane) {
  return p.s->halo + (size_t)((((lp * 2 + s) * 16 + rb) * 8 + jc) * 2 + wg) * (5 * 32) + lane;
}
__device__ __forceinline__ void load_cs(const Ctx& c, int i, Cs& cs) {
  const uint32_t a = c.sb + CSQ_OFF + i * 256 + (pin(c.lane) & 3) * 16;
#pragma unroll
  for (int j = 0; j < 4; j++) cs.v[j] = lds128f(a + j * 64);
}
template <int B, bool KEEP>
__device__ __forceinline__ void fix_box(const Ctx& c, float (&acc)[96], const Cs& cs) {
#pragma unroll
  for (int j = 0; j < 4; j++) {
    float* a = acc + 32 * B + 8 * j;
    a[0] -= c.m0 * cs.v[j].x; a[1] -= c.m0 * cs.v[j].y; a[2] -= c.m1 * cs.v[j].x; a[3] -= c.m1 * cs.v[j].y;
    a[4] -= c.m0 * cs.v[j].z; a[5] -= c.m0 * cs.v[j].w; a[6] -= c.m1 * cs.v[j].z; a[7] -= c.m1 * cs.v[j].w;
  }
#pragma unroll
  for (int i = 0; i < 32; i++) if (KEEP) keep(acc[32 * B + i]);
}
template <int B>
__device__ __forceinline__ void pack_box(const float (&acc)[96], uint32_t (&f)[16]) {
#pragma unroll
  for (int i = 0; i < 16; i++) { f[i] = pack_bf16(acc[32 * B + 2 * i], acc[32 * B + 2 * i + 1]); keep(f[i]); }
}
__device__ __forceinline__ void halo_send(const Ctx& c, int s, int part, uint32_t (&f)[16]) {
  uint4* hp = halo_ptr(c.p, c.lp, s, pin(c.rb), pin(c.jc), c.wg, pin(c.lane)) + part * 64;
  f[7] = f[7] ? f[7] : 0x8000u;
  f[15] = f[15] ? f[15] : 0x8000u;
  st_tag_if(c.wi == 3, hp, f[1], f[3], f[5], f[7]);
  st_tag_if(c.wi == 3, hp + 32, f[9], f[11], f[13], f[15]);
}
__device__ __forceinline__ void halo_clear(const Ctx& c, int s) {
  uint4* hp = halo_ptr(c.p, c.lp, s, pin(c.rb), pin(c.jc), c.wg, pin(c.lane));
#pragma unroll
  for (int i = 0; i < 4; i++) st_tag_if(c.wi == 3, hp + i * 32, 0u, 0u, 0u, 0u);
  if (!s) st_tag_if(c.wi == 3, hp + 128, __float_as_uint(c.r1), 1u, 1u, 1u);
}
__device__ __forceinline__ void put_k(const Ctx& c, const uint32_t (&k)[16]) {
  const uint32_t a = kv_base(c) + KV_K + 1024 + c.wi * 1024 + pin(c.lane) * 16;
  sts128(a, k[1], k[3], k[5], k[7]);
  sts128(a + 512, k[9], k[11], k[13], k[15]);
}
__device__ __forceinline__ void put_v(const Ctx& c, const uint32_t (&v)[16]) {
  const int lane = pin(c.lane), g = lane >> 2;
  const uint32_t a = kv_base(c) + (8 + c.wi * 16 + g) * 128 + (((lane & 3) ^ vswz(g)) << 4);
#pragma unroll
  for (int i = 0; i < 4; i++) {
    const int hh = i >> 1, rh = i & 1;
    sts128((a ^ (hh << 6)) + rh * 1024, v[8 * hh + rh], v[8 * hh + 2 + rh], v[8 * hh + 4 + rh], v[8 * hh + 6 + rh]);
  }
}
__device__ __forceinline__ void put_rstd(const Ctx& c) {
  const int lane = pin(c.lane);
  if (!(lane & 2)) sts32f(kv_base(c) + KV_R + (8 + c.wi * 16 + (lane & 1) * 8 + (lane >> 2)) * 4, (lane & 1) ? c.r1 : c.r0);
}
__device__ __forceinline__ void get_rstd(const Ctx& c, float (&rk)[4]) {
  const int lane = pin(c.lane), g = lane >> 2, j = 2 * (lane & 3);
  const uint32_t a = kv_base(c) + KV_R + (c.wi * 16 + j) * 4, a0 = a + (j <= g ? 32 : 0), a1 = a + (j + 1 <= g ? 36 : 4);
  rk[0] = lds32f(a0); rk[1] = lds32f(a1); rk[2] = lds32f(a0 + 32); rk[3] = lds32f(a1 + 32);
}
__device__ __forceinline__ void halo_wait(const Ctx& c, int s) {
  if (c.wi == 0) mbar_wait(c.sb + MISC_OFF + B_HALO + c.wg * 8, s);
}
__device__ __forceinline__ void att_ldk(const Ctx& c, Att& t) {
  const uint32_t a = kv_base(c) + KV_K + c.wi * 1024 + pin(c.lane) * 16;
  const uint4 u = lds128(a), v = lds128(a + 512);
  t.kp[0] = u.x; t.kp[1] = u.y; t.kp[2] = u.z; t.kp[3] = u.w; t.kp[4] = v.x; t.kp[5] = v.y; t.kp[6] = v.z; t.kp[7] = v.w;
}
template <int W>
__device__ __forceinline__ void att_ldv(const Ctx& c, Att& t) {
  const int lane = pin(c.lane);
  const uint32_t vb = kv_base(c) + c.wi * 2048, sw = vswz(lane & 7);
  if (W & 2) {
    const uint32_t ap = vb + (lane & 7) * 128 + (((lane >> 3) ^ sw) << 4);
    ldsm4t(ap, t.vp[0], t.vp[1], t.vp[2], t.vp[3]);
    ldsm4t(ap ^ 64, t.vp[4], t.vp[5], t.vp[6], t.vp[7]);
  }
  if (W & 1) {
    const uint32_t ao = vb + 1024 + (lane & 15) * 128 + (((lane >> 4) ^ sw) << 4);
#pragma unroll
    for (int b = 0; b < 8; b += 2) ldsm4t(ao ^ (b << 4), t.vf[2 * b], t.vf[2 * b + 1], t.vf[2 * b + 2], t.vf[2 * b + 3]);
  }
}
template <int W>
__device__ __forceinline__ void att_s(Att& t) {
#pragma unroll
  for (int ks = 0; ks < 2; ks++)
#pragma unroll
    for (int i = (W & 1) ? 0 : 4; i < ((W & 2) ? 6 : 4); i++) {
      const int hh = i & 1, kb = 2 - (i >> 1);
      const uint32_t* q = t.q + 8 * hh + 4 * ks;
      const uint32_t b0 = kb ? t.k[8 * hh + 4 * ks + kb - 1] : t.kp[4 * hh + 2 * ks], b1 = kb ? t.k[8 * hh + 4 * ks + kb + 1] : t.kp[4 * hh + 2 * ks + 1];
      if (ks) mma16816(t.s[hh][kb], q[0], q[1], q[2], q[3], b0, b1); else mma16816z(t.s[hh][kb], q[0], q[1], q[2], q[3], b0, b1);
    }
}
__device__ __forceinline__ void att_exp(const Ctx& c, Att& t, const float (&rk)[4]) {
  const int lane = pin(c.lane), g = lane >> 2, j = 2 * (lane & 3);
  const bool u0 = j <= g, u1 = j + 1 <= g, first = c.rb == 0 && c.wi == 0;
  const float sc = 0.17677669529663687f * 1.4426950408889634f;
  const float c0 = sc * c.r0, c1 = sc * c.r1;
  const float b0 = (first && !u0) ? -INFINITY : 0.f, b1 = (first && !u1) ? -INFINITY : 0.f;
  float m[4];
#pragma unroll
  for (int hh = 0; hh < 2; hh++) {
    t.v[2 * hh][0] = fmaf(u0 ? t.s[hh][1][0] : t.s[hh][0][0], c0 * rk[0], b0);
    t.v[2 * hh][1] = fmaf(u1 ? t.s[hh][1][1] : t.s[hh][0][1], c0 * rk[1], b1);
    t.v[2 * hh + 1][0] = (u0 ? t.s[hh][2][2] : t.s[hh][1][2]) * (c1 * rk[2]);
    t.v[2 * hh + 1][1] = (u1 ? t.s[hh][2][3] : t.s[hh][1][3]) * (c1 * rk[3]);
  }
#pragma unroll
  for (int i = 0; i < 4; i++) m[i] = fmaxf(t.v[i][0], t.v[i][1]);
#pragma unroll
  for (int o = 1; o <= 2; o <<= 1)
#pragma unroll
    for (int i = 0; i < 4; i++) m[i] = fmaxf(m[i], __shfl_xor_sync(0xffffffffu, m[i], o));
#pragma unroll
  for (int i = 0; i < 4; i++) {
    t.v[i][0] = ex2(t.v[i][0] - m[i]);
    t.v[i][1] = ex2(t.v[i][1] - m[i]);
    keep(t.v[i][0]);
    keep(t.v[i][1]);
  }
}
__device__ __forceinline__ void att_p(const Ctx& c, Att& t, const float (&rk)[4]) {
  const int lane = pin(c.lane), g = lane >> 2, j = 2 * (lane & 3);
  float m[4];
#pragma unroll
  for (int i = 0; i < 4; i++) m[i] = t.v[i][0] + t.v[i][1];
#pragma unroll
  for (int o = 1; o <= 2; o <<= 1)
#pragma unroll
    for (int i = 0; i < 4; i++) m[i] += __shfl_xor_sync(0xffffffffu, m[i], o);
  const uint32_t mu = (j <= g ? 0xffffu : 0u) | (j + 1 <= g ? 0xffff0000u : 0u);
#pragma unroll
  for (int i = 0; i < 4; i++) {
    const float inv = rcp(m[i]);
    const uint32_t pp = pack_bf16(t.v[i][0] * rk[2 * (i & 1)] * inv, t.v[i][1] * rk[2 * (i & 1) + 1] * inv);
    t.p[i >> 1][(i & 1) * 2] = pp & ~mu;
    t.p[i >> 1][(i & 1) * 2 + 1] = pp & mu;
    keep(t.p[i >> 1][(i & 1) * 2]);
    keep(t.p[i >> 1][(i & 1) * 2 + 1]);
  }
}
__device__ __forceinline__ void att_pv(Att& t) {
#pragma unroll
  for (int b = 0; b < 8; b++) mma1688z(t.o[b], t.p[b >> 2][0], t.vp[b]);
#pragma unroll
  for (int b = 0; b < 8; b++) mma16816(t.o[b], t.p[b >> 2][1], t.p[b >> 2][2], 0u, t.p[b >> 2][3], t.vf[2 * b], t.vf[2 * b + 1]);
}
template <bool LOCAL>
__device__ __forceinline__ void att_out(const Ctx& c, int s, const Att& t) {
  const int lane = pin(c.lane), g = lane >> 2, tq = lane & 3;
  __nv_bfloat16* dst = c.p.s->o + (size_t)seq_row(c, g) * DM + (s * 8 + pin(c.jc)) * 64 + tq * 8;
  const uint32_t la = warp_rows(c) + g * 128 + ((tq ^ g) << 4);
  uint32_t v[16];
#pragma unroll
  for (int i = 0; i < 4; i++) {
    const int hh = i & 1, rh = i >> 1;
#pragma unroll
    for (int b = 0; b < 4; b++) v[4 * i + b] = pack_bf16(t.o[4 * hh + b][2 * rh], t.o[4 * hh + b][2 * rh + 1]);
  }
#pragma unroll
  for (int i = 0; i < 4; i++) stg128(dst + (i >> 1) * 16 * DM + (i & 1) * 32, v[4 * i], v[4 * i + 1], v[4 * i + 2], v[4 * i + 3]);
  carrive(c, B_DONE + c.wg * 8);
  if (LOCAL) {
#pragma unroll
    for (int i = 0; i < 4; i++) sts128((la ^ ((i & 1) << 6)) + (i >> 1) * 1024, v[4 * i], v[4 * i + 1], v[4 * i + 2], v[4 * i + 3]);
  }
}
__device__ __forceinline__ void halo_go(const Ctx& c) {
  if (c.wi == 0 && c.lane == 0) mbar_arrive(c.sb + MISC_OFF + B_HGO + c.wg * 8);
}

__device__ __forceinline__ void phase_a(Ctx& c, Stage& s) {
  float O[64];
  const uint32_t misc = c.sb + MISC_OFF, stag = c.lp * 2 + 1;
  Att t;
  float rk[4];
  {
    float U[96], V[96];
    step1<true, true>(c, s, V, Nop());
    step1<false, false>(c, s, V, Nop());
    step1<true, false>(c, s, U, Nop());
    {
      Stats st;
      st.a = st.b = st.c = st.d = make_float2(0.f, 0.f);
#pragma unroll 1
      for (int k = 0; k < 9; k++)
        step1<false, false, 2>(c, s, U, [&]() {
          if (k == 2) mbar_wait(misc + B_XL, 0);
          if (k >= 3 && k < 7) stats_acc(c, k - 3, st);
          if (k == 6) stats_store(c, st, stag);
        });
      step1<false, false>(c, s, U, [&]() { load_stats(c, st); });
      step1<false, false>(c, s, U, Nop());
      step1<false, false>(c, s, U, [&]() { combine_stats(c, st, stag); mbar_wait(misc + B_CSQ + 8, 0); });
    }
#pragma unroll 1
    for (int k = 0; k < 3; k++) {
      Cs cs;
      load_cs(c, 3 + k, cs);
      step1<false, false, 2>(c, s, U, [&]() {
        if (k & 2) { fix_box<2, true>(c, V, cs); mbar_wait(misc + B_CSQ, 0); }
        else if (k & 1) fix_box<1, true>(c, V, cs);
        else { halo_clear(c, 0); fix_box<0, true>(c, V, cs); }
      });
    }
    {
      Cs cs;
      load_cs(c, 1, cs);
      step1<false, false>(c, s, V, [&]() { keep_all(U); fix_box<1, false>(c, U, cs); pack_box<1>(U, t.k); halo_send(c, 0, 0, t.k); put_k(c, t.k); });
      step1<false, false>(c, s, V, [&]() { load_cs(c, 2, cs); fix_box<2, false>(c, U, cs); pack_box<2>(U, t.vf); halo_send(c, 0, 1, t.vf); put_v(c, t.vf); load_cs(c, 0, cs); halo_go(c); });
      step1<false, false>(c, s, V, [&]() { fix_box<0, false>(c, U, cs); pack_box<0>(U, t.q); put_rstd(c); });
    }
    step1<false, false>(c, s, V, [&]() { halo_clear(c, 1); });
    step1<false, false>(c, s, V, [&]() { bar_sync(2 + c.wg, 128); halo_wait(c, 0); att_ldk(c, t); get_rstd(c, rk); });
    att_s<3>(t);
    step1<false, false>(c, s, V, [&]() { att_exp(c, t, rk); });
    step1<false, false>(c, s, V, [&]() { att_ldv<3>(c, t); att_p(c, t, rk); });
    att_pv(t);
    step1<false, false>(c, s, V, [&]() { att_out<false>(c, 0, t); });
    step1<false, false>(c, s, V, [&]() { resid_init<0>(c, O); });
    step1<false, false>(c, s, V, [&]() { resid_init<1>(c, O); });
#pragma unroll 1
    for (int k = 0; k < 4; k++) step1<false, false>(c, s, V, Nop());
    wgmma_wait<0>();
    release(c);
    keep_all(V);
    pack_box<1>(V, t.k); halo_send(c, 1, 0, t.k); put_k(c, t.k);
    pack_box<2>(V, t.vf); halo_send(c, 1, 1, t.vf); put_v(c, t.vf);
    pack_box<0>(V, t.q);
  }
  step1<false, true, 2>(c, s, O, [&]() { halo_go(c); });
  step1<false, false>(c, s, O, Nop());
  wgmma_wait<0>();
  release(c);
  bar_sync(1, 256);
  cut(s);
  att_ldv<1>(c, t);
  att_s<1>(t);
  halo_wait(c, 1);
  att_ldk(c, t);
  att_ldv<2>(c, t);
  att_s<2>(t);
  att_exp(c, t, rk);
  att_p(c, t, rk);
  att_pv(t);
  att_out<true>(c, 1, t);
  bar_sync(1, 256);
  step1<false, true>(c, s, O, Nop());
#pragma unroll 1
  for (int k = NOA + 1; k < 16; k++)
    step1<false, false, 2>(c, s, O, [&]() {
      if (k == 6) { fence_proxy_async_smem(); bar_sync(2 + c.wg, 128); }
    });
  finish_x(c, O, c.p.s->x);
}

template <int H>
__device__ __forceinline__ void scale_to(const Ctx& c, float (&E)[64], float (&A)[64]) {
  const float h0 = 0.5f * c.r0, h1 = 0.5f * c.r1;
#pragma unroll
  for (int i = (H & 1) ? 0 : 32; i < ((H & 2) ? 64 : 32); i++) {
    keep(A[i]);
    E[i] = A[i] * (i < 32 ? ((i & 2) ? h1 : h0) : ((i & 2) ? c.r1 : c.r0));
    keep(E[i]);
  }
}
template <int B>
__device__ __forceinline__ void piece(const Ctx& c, float (&A)[64], const float4 cs) {
  float h[4];
#pragma unroll
  for (int e = 0; e < 4; e++) {
    const float n = (e & 2) ? c.m1 : c.m0;
    const float a = fmaf(n, (e & 1) ? cs.y : cs.x, A[4 * B + e]), u = fmaf(n, (e & 1) ? cs.w : cs.z, A[32 + 4 * B + e]);
    const float w = a * u;
    h[e] = fmaf(w, tanh_approx(a), w);
  }
  A[4 * B] = __uint_as_float(pack_bf16(h[0], h[1]));
  A[4 * B + 1] = __uint_as_float(pack_bf16(h[2], h[3]));
  if (B == 7) carrive(c, B_CSFREE);
}
template <int B>
__device__ __forceinline__ void piece2(const Ctx& c, float (&E)[64], const float4 c0, const float4 c1) {
  piece<B>(c, E, c0);
  piece<B + 1>(c, E, c1);
}
template <int Q>
__device__ __forceinline__ void store_h2(const Ctx& c, const float (&E)[64], int blk) {
  const int lane = pin(c.lane);
  __nv_bfloat16* dst = c.p.s->h + (size_t)seq_row(c, lane >> 2) * FF + (blk * 8 + pin(c.jc)) * 64 + Q * 32 + (lane & 3) * 8;
#pragma unroll
  for (int rh = 0; rh < 2; rh++)
    stg128(dst + rh * 16 * FF, __float_as_uint(E[16 * Q + rh]), __float_as_uint(E[16 * Q + 4 + rh]),
           __float_as_uint(E[16 * Q + 8 + rh]), __float_as_uint(E[16 * Q + 12 + rh]));
}
__device__ __forceinline__ void tail_piece(const Ctx& c, float (&A)[64], const float4 cs, int k, int blk) {
  if (k < 4) {
    if (k < 2) { if (k == 0) piece<0>(c, A, cs); else piece<1>(c, A, cs); }
    else { if (k == 2) piece<2>(c, A, cs); else { piece<3>(c, A, cs); store_h2<0>(c, A, blk); } }
  } else {
    if (k < 6) { if (k == 4) piece<4>(c, A, cs); else piece<5>(c, A, cs); }
    else { if (k == 6) piece<6>(c, A, cs); else { piece<7>(c, A, cs); store_h2<1>(c, A, blk); } }
  }
}
template <int LOFF>
__device__ __forceinline__ void drain(Ctx& c, Stage& s, float (&L)[64], float (&M)[64], float (&E)[64]) {
  wait_full(c);
  wgmma_fence();
  stage128<false>(M, s.da, s.db + (1024 - LOFF));
  wgmma_commit();
  wgmma_wait<1>();
  release(c);
  scale_to<3>(c, E, L);
  wgmma_fence();
  stage128<true>(L, s.da, s.db + LOFF);
  wgmma_commit();
  s = peek(c);
}
__device__ __forceinline__ void phase_b(Ctx& c, Stage& s) {
  float X[64], Y[64], E[64];
  const uint32_t stag = (c.lp * 2 + 2) & 3;
  step1<true, true>(c, s, X, Nop());
  step1<false, false>(c, s, X, Nop());
  {
    Stats st;
    st.a = st.b = st.c = st.d = make_float2(0.f, 0.f);
    step2<true>(c, s, E, Y, Nop());
#pragma unroll 1
    for (int k = 0; k < 5; k++)
      step2<false, 2>(c, s, E, Y, [&]() {
        if (k < 4) stats_acc(c, k, st);
        if (k == 3) stats_store(c, st, stag);
      });
    step2<false>(c, s, E, Y, [&]() { load_stats(c, st); });
    step2<false>(c, s, E, Y, Nop());
    step2<false>(c, s, E, Y, [&]() { combine_stats(c, st, stag); c.m0 *= -c.r0; c.m1 *= -c.r1; });
  }
#pragma unroll 1
  for (int k = 0; k < 7; k++) step1<false, false>(c, s, E, Nop());
  step2<false, 0>(c, s, X, Y, [&]() { scale_to<3>(c, E, E); });
#pragma unroll 1
  for (int blk = 0;; blk++) {
    mbar_wait(c.sb + MISC_OFF + B_CS, (blk + c.lp) & 1);
    const int n = blk == 2 ? 8 : 6;
#pragma unroll 1
    for (int k = 0; k < n; k++) {
      const uint32_t ca = c.sb + CSG_OFF + (k & 3) * 128 + (pin(c.lane) & 3) * 16;
      const float4 c0 = lds128f(ca), c1 = lds128f(ca + 64);
      step2<false, 2>(c, s, X, Y, [&]() {
        if (k & 4) {
          if (!(k & 3)) store_h2<0>(c, E, blk);
          else if (k == 5) { store_h2<1>(c, E, blk); if (blk == 3) carrive(c, B_DONE + c.wg * 8); }
        } else if (k & 2) {
          if (k & 1) piece2<6>(c, E, c0, c1); else piece2<4>(c, E, c0, c1);
        } else {
          if (k & 1) piece2<2>(c, E, c0, c1); else piece2<0>(c, E, c0, c1);
        }
      });
    }
    if (blk == 4) break;
    if (blk & 1) drain<0>(c, s, X, Y, E); else drain<1024>(c, s, Y, X, E);
  }
  step2<false>(c, s, X, Y, [&]() { resid_init<0>(c, E); });
  step2<false>(c, s, X, Y, [&]() { resid_init<1>(c, E); mbar_wait(c.sb + MISC_OFF + B_CS, (5 + c.lp) & 1); });
  step1<false, false>(c, s, X, [&]() { scale_to<1>(c, Y, Y); });
  step1<false, false>(c, s, X, [&]() { scale_to<2>(c, Y, Y); });
#pragma unroll 1
  for (int blk = 5;; blk++) {
#pragma unroll 1
    for (int k = 0; k < 8; k++) {
      const float4 cs = lds128f(c.sb + CSG_OFF + k * 64 + (pin(c.lane) & 3) * 16);
      if (blk == 5 && k < 5) step1<false, false, 0>(c, s, X, Nop()); else step1<false, false, 0>(c, s, E, Nop());
      tail_piece(c, Y, cs, k, blk);
      wgmma_wait<1>();
    }
    if (blk == 6) break;
    step1<false, false>(c, s, E, [&]() { scale_to<1>(c, Y, X); });
    step1<false, false>(c, s, E, [&]() { scale_to<2>(c, Y, X); mbar_wait(c.sb + MISC_OFF + B_CS, c.lp & 1); });
  }
  carrive(c, B_DONE + c.wg * 8);
#pragma unroll 1
  for (int k = 0; k < 43; k++) step1<false, false>(c, s, E, Nop());
  finish_x(c, E, c.lp ? c.p.out : c.p.s->x);
}

__device__ __forceinline__ void acc8(float (&a)[8], const uint4& v) {
  a[0] += bf_lo(v.x); a[1] += bf_hi(v.x); a[2] += bf_lo(v.y); a[3] += bf_hi(v.y);
  a[4] += bf_lo(v.z); a[5] += bf_hi(v.z); a[6] += bf_lo(v.w); a[7] += bf_hi(v.w);
}
__device__ __forceinline__ void st_sums(uint4* dst, const float (&a)[8], uint32_t tag) {
  uint32_t u[8];
#pragma unroll
  for (int i = 0; i < 8; i++) u[i] = (__float_as_uint(a[i]) & ~1u) | ((tag >> (i & 3)) & 1u);
  st_tag(dst, u[0], u[1], u[2], u[3]);
  st_tag(dst + 1, u[4], u[5], u[6], u[7]);
}
__device__ __forceinline__ bool add_sum(float4& a, const uint4& v, uint32_t tag) {
  a.x += __uint_as_float(v.x & ~1u); a.y += __uint_as_float(v.y & ~1u);
  a.z += __uint_as_float(v.z & ~1u); a.w += __uint_as_float(v.w & ~1u);
  return ((v.x & 1) | (v.y & 1) << 1 | (v.z & 1) << 2 | (v.w & 1) << 3) == (tag & 15);
}

__device__ __forceinline__ void spare_sum(const Params& p, uint32_t sb, int d, int w, int lane) {
  const int chunk = (w & 1) * 4 + (lane & 3), rg = lane >> 2;
  const uint32_t base = sb + (w >> 1) * 8192 + rg * 128 + ((chunk ^ rg) << 4);
  uint32_t slot = 0, par = 0;
#pragma unroll 1
  for (int t = d; t < 28; t += 4) {
    float a[8] = {0, 0, 0, 0, 0, 0, 0, 0};
#pragma unroll 1
    for (int k = 0; k < 16; k++) {
      mbar_wait_idle(sb + MISC_OFF + B_SFULL + slot * 8, par);
      uint4 v[8];
#pragma unroll
      for (int r = 0; r < 8; r++) v[r] = lds128(base + slot * 32768 + r * 1024);
#pragma unroll
      for (int r = 0; r < 8; r++) acc8(a, v[r]);
      __syncwarp();
      if (lane == 0) mbar_arrive(sb + MISC_OFF + B_SEMPTY + slot * 8);
      if (++slot == 6) { slot = 0; par ^= 1; }
    }
#pragma unroll 1
    for (int o = 16; o >= 4; o >>= 1)
#pragma unroll
      for (int i = 0; i < 8; i++) a[i] += __shfl_xor_sync(0xffffffffu, a[i], o);
    if (lane < 4) st_sums(p.s->part + (3 * DM + ((w >> 1) & 1) * FF + t * 128 + (w >> 2) * 64 + (w & 1) * 32) / 4 + lane * 2, a, ld_tag_s(sb));
  }
}
__device__ __forceinline__ void spare_load(const Params& p, uint32_t sb, int d, int lane) {
  uint32_t slot = 0, par = 1;
  const uint32_t want = ld_epoch(p) * 2 + 1, t0 = clock();
  while ((uint32_t)clock() - t0 < 13000) __nanosleep(200);
#pragma unroll 1
  for (int t = d; t < 28; t += 4) {
    if ((t >> 2) == 2) {
#pragma unroll 1
      for (uint32_t i = 0, n = 0; i < 4;) {
        const uint32_t v = ld_flag(reinterpret_cast<const uint8_t*>(p.s->flags + (i * 4 + (lane >> 3)) * 8 + F_X1B - 1) + (lane & 7) * 2);
        if (__all_sync(0xffffffffu, ((v - want) & 255) < 2)) i++; else __nanosleep(300);
        if (++n > (1u << 20)) __trap();
      }
    }
#pragma unroll 1
    for (int k = 0; k < 16; k++) {
      const uint32_t bar = sb + MISC_OFF + B_SFULL + slot * 8;
      mbar_wait(sb + MISC_OFF + B_SEMPTY + slot * 8, par);
      if (elect_one()) {
        mbar_expect_tx(bar, 32768);
#pragma unroll
        for (int b = 0; b < 4; b++) tma_load(sb + slot * 32768 + b * 8192, (b & 1) ? &p.wu : &p.wg, bar, t * 128 + (b >> 1) * 64, k * 64);
      }
      if (++slot == 6) { slot = 0; par ^= 1; }
    }
  }
}
__device__ __forceinline__ uint32_t qkv_sums(const Params& p, uint32_t sb, int q, int rb, int jc, int lane) {
  const uint32_t bar = sb + MISC_OFF + B_SLAB + q * 8, buf = sb + KV_OFF + q * 8192;
  const uint32_t tag = ld_epoch(p) + 1;
  mbar_wait_idle(sb + MISC_OFF + B_FULL, 0);
  const uint32_t t0 = clock();
  if (q == 0) {
    const int gx = (jc >> 1) - 1;
    if (gx >= 0) mbar_wait_idle(sb + MISC_OFF + B_EMPTY + gx * 8, 0);
    if (elect_one()) {
      mbar_expect_tx(sb + MISC_OFF + B_XL, 32768);
      tma_load3(sb + STG_OFF, &p.x0, sb + MISC_OFF + B_XL, jc * 128, rb * 64);
      tma_load3(sb + STG_OFF + 16384, &p.x0, sb + MISC_OFF + B_XL, jc * 128 + 64, rb * 64);
    }
  }
  {
    const int col = q * DM + ((rb & 1) * 8 + jc) * 64;
    float a[8] = {0.f, 0.f, 0.f, 0.f, 0.f, 0.f, 0.f, 0.f};
#pragma unroll 1
    for (int h = 0; h < 2; h++) {
      while (h && (uint32_t)clock() - t0 < 4600) __nanosleep(100);
      if (elect_one()) {
        mbar_expect_tx(bar, 8192);
        tma_load(buf, &p.wqkv, bar, col, ((rb & 14) + h) * 64);
        tma_load(buf + 4096, &p.wqkv, bar, col, ((rb & 14) + h) * 64 + 32);
      }
      mbar_wait_idle(bar, h);
      const uint32_t base = buf + (lane >> 3) * 128 + (((lane & 7) ^ (lane >> 3)) << 4);
#pragma unroll 1
      for (int r = 0; r < 8; r += 2) {
        const uint4 v0 = lds128(base + r * 1024), v1 = lds128((base ^ 64) + r * 1024 + 512);
        const uint4 v2 = lds128(base + r * 1024 + 1024), v3 = lds128((base ^ 64) + r * 1024 + 1536);
        acc8(a, v0); acc8(a, v1); acc8(a, v2); acc8(a, v3);
      }
      fence_proxy_async_smem();
      __syncwarp();
    }
#pragma unroll 1
    for (int o = 8; o <= 16; o <<= 1)
#pragma unroll
      for (int j = 0; j < 8; j++) a[j] += __shfl_xor_sync(0xffffffffu, a[j], o);
    if (lane < 8) st_sums(p.s->part + ((rb >> 1) * NCS + col) / 4 + lane * 2, a, tag);
  }
#pragma unroll 1
  for (int s = 1; s >= 0; s--) {
    const uint4* src = p.s->part + ((lane >> 4) * 4 * NCS + q * DM + (s * 8 + jc) * 64) / 4 + (lane & 15);
    float4 a;
    uint32_t n = 0;
    while (true) {
      uint4 v[4];
#pragma unroll
      for (int r = 0; r < 4; r++) v[r] = ld_tag(src + r * (NCS / 4));
      a = make_float4(0.f, 0.f, 0.f, 0.f);
      bool ok = true;
#pragma unroll
      for (int r = 0; r < 4; r++) ok = add_sum(a, v[r], tag) && ok;
      if (__all_sync(0xffffffffu, ok)) break;
      if (++n > (1u << 18)) __trap();
    }
    a.x += __shfl_xor_sync(0xffffffffu, a.x, 16); a.y += __shfl_xor_sync(0xffffffffu, a.y, 16);
    a.z += __shfl_xor_sync(0xffffffffu, a.z, 16); a.w += __shfl_xor_sync(0xffffffffu, a.w, 16);
    const uint32_t dst = sb + CSQ_OFF + (s * 3 + q) * 256 + ((lane & 15) >> 2) * 64 + (lane & 1) * 32 + (lane & 2) * 4 + (lane >> 4) * 16;
    sts64f(dst, lane < 16 ? a.x : a.z, lane < 16 ? a.y : a.w);
    __syncwarp();
    if (lane == 0) mbar_arrive(sb + MISC_OFF + B_CSQ + s * 8);
  }
  return tag;
}

struct Prod {
  const Params& p;
  uint32_t sb, it;
  uint32_t seq, kb, kinc;
};
__device__ __forceinline__ uint32_t seg_begin(Prod& pr, int sg, int jc) {
  const uint32_t d = pr.p.t.seg[sg], ks = (d >> 19) & 7;
  pr.seq = pr.p.t.seq[sg < 6 ? 8 : jc][ks];
  pr.kinc = ks == K_LIN;
  pr.kb = ks == K_LIN ? ((d >> 13) & 7) * 8 : 0;
  return d;
}
__device__ __forceinline__ int next_k(Prod& pr) {
  const int k = (pr.kb + (pr.seq & 15)) * 64;
  pr.seq >>= 4;
  pr.kb += pr.kinc;
  return k;
}
__device__ __forceinline__ void wait_released(const Prod& pr, uint32_t lag) {
  const uint32_t j = pr.it - lag;
  mbar_wait(pr.sb + MISC_OFF + B_EMPTY + (j & 7) * 8, (j >> 3) & 1);
}
template <int NB>
__device__ __forceinline__ void produce_b(Prod& pr, int n, uint32_t bytes, const CUtensorMap* tb, int c0, int c1, uint32_t rank,
                                          const CUtensorMap* ta, int arow) {
#pragma unroll 1
  for (; n > 0; n--) {
    const uint32_t e = pr.p.t.ring[pr.it];
    const int k = pin(next_k(pr));
    const uint32_t bar = pin(pr.sb + MISC_OFF + B_FULL + (pr.it & 7) * 8);
    const uint32_t b = pin(pr.sb + ((e >> 16) << 4) + rank * (NB == 3 ? 4096 : 8192));
    wait_released(pr, e & 15);
    if (elect_one()) {
      mbar_expect_tx(bar, bytes);
      if (NB == 3) {
#pragma unroll
        for (int q = 0; q < 3; q++) tma_load_mc(b + q * 8192, tb, bar, q * DM + c0, k + rank * 32);
        if (ta) tma_load3(pr.sb + ((e & 0x3e00) << 4), ta, bar, k, arow);
      } else if (NB == 5) {
        tma_load5_mc(b, tb, bar, c0, k >> 5);
      } else {
        tma_load_mc(b, tb, bar, c0, k);
        if (NB == 4) tma_load_mc(b + 16384, tb, bar, c1, k);
      }
    }
    pr.it++;
  }
}
__device__ __forceinline__ void cs_fill(const Params& p, uint32_t sb, int i, int jc, int lane, uint32_t tag) {
  const int blk = i >= 7 ? i - 7 : i, m = lane & 15;
  const uint4* src = p.s->part + (3 * DM + (lane >> 4) * FF + (blk * 8 + jc) * 64) / 4 + m;
  float4 a;
  uint32_t n = 0;
  while (true) {
    a = make_float4(0.f, 0.f, 0.f, 0.f);
    if (__all_sync(0xffffffffu, add_sum(a, ld_tag(src), tag))) break;
    if (++n > (1u << 18)) __trap();
    __nanosleep(500);
  }
  if (i > 0) mbar_wait_idle(sb + MISC_OFF + B_CSFREE, (i - 1) & 1);
  const float f = lane < 16 ? 0.5f : 1.f;
  const uint32_t dst = sb + CSG_OFF + m * 32 + (lane >> 4) * 8;
  sts64f(dst, a.x * f, a.y * f);
  sts64f(dst + 16, a.z * f, a.w * f);
  __syncwarp();
  if (lane == 0) mbar_arrive(sb + MISC_OFF + B_CS);
}

template <bool BY_SM>
__global__ void __cluster_dims__(2, 1, 1) __launch_bounds__(384, 1)
fused_kernel(const __grid_constant__ Params p) {
  extern __shared__ __align__(1024) uint8_t smem_raw[];
  const uint32_t sb = smem_u32(smem_raw);
  const uint32_t misc = sb + MISC_OFF;
  const int warp = __shfl_sync(0xffffffffu, threadIdx.x >> 5, 0), lane = threadIdx.x & 31;
  uint32_t smid;
  asm volatile("mov.u32 %0, %%smid;" : "=r"(smid));
  const int tpc = smid >> 1;
  const int cl = __shfl_sync(0xffffffffu, !BY_SM ? (int)blockIdx.x >> 1 : tpc < 32 ? tpc
                           : tpc < 60 ? (4 + (tpc - 32) / 7) * 8 + 1 + (tpc - 32) % 7 : tpc < 62 ? tpc + 4 : (tpc - 58) * 8, 0);
  const uint32_t rank = blockIdx.x & 1;
  const int cta = cl * 2 + rank;
  const bool spare = cta >= NCTA;
  const int rb = (7 - (cl & 7)) * 2 + rank, jc = (cl >> 3) & 7;

  if (warp < 8) {
    if (warp < 2 && elect_one()) asm volatile("prefetch.tensormap [%0];" ::"l"(warp ? &p.x0 : &p.wqkv) : "memory");
    cluster_arrive();
    uint32_t tag = ld_epoch(p) + 1;
    cluster_wait();
    asm volatile("setmaxnreg.inc.sync.aligned.u32 232;");
    asm volatile("st.shared.u32 [%0], %1;" ::"r"(misc + M_TAG), "r"(tag) : "memory");
    if (spare) {
      spare_sum(p, sb, cta - NCTA, warp, lane);
      cluster_arrive();
    } else {
      Ctx c{p};
      c.sb = sb; c.w = warp; c.wg = warp >> 2; c.wi = warp & 3; c.lane = lane; c.rb = rb; c.jc = jc;
      c.rel = c.wi == 0 && lane < 2;
      asm("mapa.shared::cluster.u32 %0, %1, %2;" : "=r"(c.ebar) : "r"(misc + B_EMPTY), "r"(lane & 1));
      c.da = (((sb + c.wg * 8192) & 0x3FFFF) >> 4) | (1u << 16);
      c.db = ((sb & 0x3FFFF) >> 4) | ((8192u >> 4) << 16);
      c.it = 0;
      Stage s = peek(c);
#pragma unroll 1
      for (c.lp = 0; c.lp < 2; c.lp++) {
        phase_a(c, s);
        phase_b(c, s);
      }
      store_box(c, p.out, 1);
    }
  } else {
    asm volatile("setmaxnreg.dec.sync.aligned.u32 40;");
    if (elect_one()) {
      if (warp == 10) {
        for (int i = 0; i < 8; i++) mbar_init(misc + B_FULL + i * 8, 1);
      } else if (warp == 9) {
        if (sb & 1023) __trap();
        for (int i = 0; i < 8; i++) mbar_init(misc + B_EMPTY + i * 8, 4);
      } else if (warp == 8) {
        for (int i = 0; i < 2; i++) { mbar_init(misc + B_DONE + i * 8, 4); mbar_init(misc + B_HGO + i * 8, 1); mbar_init(misc + B_HALO + i * 8, 1); mbar_init(misc + B_CSQ + i * 8, 3); }
        mbar_init(misc + B_CS, 1); mbar_init(misc + B_XL, 1); mbar_init(misc + B_BOX1, 8); mbar_init(misc + B_CSFREE, 8);
      } else {
        for (int i = 0; i < 6; i++) { mbar_init(misc + B_SFULL + i * 8, 1); mbar_init(misc + B_SEMPTY + i * 8, 8); }
      }
      asm volatile("fence.mbarrier_init.release.cluster;" ::: "memory");
    }
    cluster_arrive();
    if (warp == 10 && !spare && elect_one()) {
      mbar_expect_tx(misc + B_FULL, 40960);
      tma_load3(sb + ((RING0 & 0x3e00) << 4), &p.x0, misc + B_FULL, 0, rb * 64);
#pragma unroll
      for (int i = 0; i < 6; i++) tma_load(sb + ((RING0 >> 16) << 4) + i * 4096, &p.wqkv, misc + B_FULL, (i >> 1) * DM + (8 + jc) * 64, (i & 1) * 32);
#pragma unroll 1
      for (int i = 1; i < 4; i++) tma_load3(sb + ((p.t.ring[i] & 0x3e00) << 4), &p.x0, misc + B_FULL + i * 8, (i & 1) * 64, rb * 64);
    }
    cluster_wait();
    if (spare) {
      if (warp == 8) {
        spare_load(p, sb, cta - NCTA, lane);
      }
    } else if (warp == 8) {
      Prod pr{p};
      pr.sb = sb; pr.it = 0;
#pragma unroll 1
      for (int sg = 0; sg < 2 * NSEG; sg++) {
        const uint32_t d = seg_begin(pr, sg, jc);
        if (sg == 0) { pr.seq >>= 4; pr.it = 1; }
        const int n = (d & 63) - (sg == 0), nb = (d >> 6) & 7, am = (d >> 9) & 3, wm = (d >> 11) & 3;
        const CUtensorMap* tb = &p.wqkv + (wm == W_D ? 4 : wm == W_G ? 2 + rank : wm);
        const int c0 = (wm & 1) ? jc * 128 + rank * 64 : (((d >> 13) & 7) * 8 + jc) * 64, c1 = (((d >> 16) & 7) * 8 + jc) * 64;
        const uint32_t bytes = nb * 8192 + (am ? 16384 : 0);
        if (nb == 3) produce_b<3>(pr, n, bytes, tb, c0, c1, rank, sg < 6 && sg > 1 ? &p.x0 : nullptr, rb * 64);
        else if (nb == 4) produce_b<4>(pr, n, bytes, tb, c0, c1, rank, nullptr, 0);
        else if (wm == W_D) produce_b<5>(pr, n, bytes, tb, c0, c1, rank, nullptr, 0);
        else produce_b<2>(pr, n, bytes, tb, c0, c1, rank, nullptr, 0);
      }
    } else {
      const uint32_t tag = qkv_sums(p, sb, warp - 9, rb, jc, lane);
      if (warp == 10) {
        Prod pr{p};
        pr.sb = sb; pr.it = 32;
        const uint8_t* fl = reinterpret_cast<const uint8_t*>(p.s->flags + rb * 8) + (lane & 15);
        mbar_wait_idle(misc + B_DONE, 0);
        uint32_t early = ~0u;
#pragma unroll 1
        for (int sg = 6; sg < 2 * NSEG; sg++) {
          const uint32_t d = seg_begin(pr, sg, jc), dep = d >> 22, am = (d >> 9) & 3;
          if (!am) { pr.it += d & 63; early = ~0u; continue; }
          const uint32_t want = (tag * 2 - (sg < NSEG)) & 255;
          uint32_t ready = dep ? __ballot_sync(0xffffffffu, early == want) : ~0u;
          if (dep) fence_proxy_async();
#pragma unroll 1
          for (int n = d & 63; n > 0; n--) {
            const uint32_t e = pr.p.t.ring[pr.it];
            const int k = pin(next_k(pr));
            const uint32_t bar = pin(misc + B_FULL + (pr.it & 7) * 8), a = pin(sb + ((e & 0x3e00) << 4));
            if (n == 1 && (pr.p.t.seg[sg + 1] >> 22)) early = ld_flag(fl + ((pr.p.t.seg[sg + 1] >> 22) - 1) * 16);
            if (am == A_X) wait_released(pr, (e >> 4) & 15);
            if (ready != ~0u) {
              const uint32_t need = (am == A_H || n == 1) ? ~0u : 3u << (am == A_X ? (k >> 6) & 14 : (k >> 5) & 14);
              if ((ready & need) != need) {
                const uint8_t* f = fl + (dep - 1) * 16;
                uint32_t v0 = ld_flag(f);
                const uint32_t t0 = clock();
                while ((uint32_t)clock() - t0 < 120) {}
                for (uint32_t i = 0;; i++) {
                  const uint32_t v1 = ld_flag(f);
                  ready = __ballot_sync(0xffffffffu, v0 == want);
                  if ((ready & need) == need) break;
                  v0 = ld_flag(f);
                  ready = __ballot_sync(0xffffffffu, v1 == want);
                  if ((ready & need) == need) break;
                  if (i > (1u << 19)) __trap();
                }
                fence_proxy_async();
              }
            }
            if (am != A_X) wait_released(pr, (e >> 4) & 15);
            if (elect_one()) tma_load3(a, &p.x0 + am, bar, k, rb * 64);
            pr.it++;
          }
        }
      } else {
        const int w = (warp - 9) >> 1;
        int ncs = 0;
#pragma unroll 1
        for (int ev = 0; ev < 14; ev++) {
          const int layer = ev >> 3, e = ev & 7;
          if (e < 2) {
            uint4* hp = halo_ptr(p, layer, e, rb - 1, jc, w, pin(lane));
            mbar_wait_idle(misc + B_HGO + w * 8, e);
            uint4 v[5];
            uint32_t n = 0;
#pragma unroll
            for (int i = 0; i < 5; i++) v[i] = make_uint4(0, 0, 0, 0);
            while (rb > 0) {
#pragma unroll
              for (int i = 0; i < 4; i++) v[i] = ld_tag(hp + i * 32);
              if (!e) v[4] = ld_tag(hp + 128);
              if (__all_sync(0xffffffffu, v[0].w && v[1].w && v[2].w && v[3].w && (e || v[4].w))) break;
              if (++n > (1u << 18)) __trap();
            }
            const int l = pin(lane);
            const uint32_t kv = sb + KV_OFF + w * KV_WG, d0 = kv + (l >> 2) * 128 + (((l & 3) ^ vswz(l >> 2)) << 4);
            sts128(kv + KV_K + l * 16, v[0].x, v[0].y, v[0].z, v[0].w);
            sts128(kv + KV_K + 512 + l * 16, v[1].x, v[1].y, v[1].z, v[1].w);
            sts128(d0, v[2].x, v[2].y, v[2].z, v[2].w);
            sts128(d0 ^ 64, v[3].x, v[3].y, v[3].z, v[3].w);
            if (!e) sts32f(kv + KV_R + (l >> 2) * 4, __uint_as_float(v[4].x));
            __syncwarp();
            if (lane == 0) mbar_arrive(misc + B_HALO + w * 8);
          }
          if (w == 1) {
            const int c1 = ev == 2 ? 1 : e == 4 ? 5 + 7 * layer : e == 5 ? 8 + 6 * layer : 0;
#pragma unroll 1
            for (; ncs < c1; ncs++) cs_fill(p, sb, ncs, jc, lane, tag);
          }
          uint8_t* flag = reinterpret_cast<uint8_t*>(p.s->flags + rb * 8 + e) + jc * 2;
          if ((e & 3) == 3) {
            if (w == 0 && lane == 0) {
              mbar_wait(misc + B_BOX1, (ev >> 2) & 1);
              mbar_wait(misc + B_FULL + 4 * 8, ev > 3);
              tma_store3(&p.x, sb + STG_OFF + 16384, jc * 128 + 64, rb * 64);
              fence_gpu();
              st_flags(flag, tag * 2 - (ev < 6));
            }
            continue;
          }
          mbar_wait_idle(misc + B_DONE + w * 8, (ev - (ev >> 2)) & 1);
          if (lane == 0) {
            if (w == 1) {
              mbar_wait(misc + B_DONE, (ev - (ev >> 2)) & 1);
              fence_gpu();
              st_flags(flag, tag * 2 - (ev < 6));
            }
          }
          if (e < 2 && rb > 0) {
            __syncwarp();
            uint4* hp = halo_ptr(p, layer, e, rb - 1, jc, w, pin(lane));
#pragma unroll 1
            for (int i = 0; i < 5; i++) st_tag(hp + i * 32, 0u, 0u, 0u, 0u);
          }
        }
      }
    }
    __syncwarp();
    if (BY_SM) {
      uint32_t nsmid;
      asm volatile("mov.u32 %0, %%nsmid;" : "=r"(nsmid));
      if (nsmid != 132) __trap();
    }
    if (threadIdx.x == 256) p.s->epoch[blockIdx.x] = ld_tag_s(sb);
    cluster_arrive();
  }
  cluster_wait();
}

typedef CUresult (*EncodeFn)(CUtensorMap*, CUtensorMapDataType, cuuint32_t, void*, const cuuint64_t*, const cuuint64_t*,
                             const cuuint32_t*, const cuuint32_t*, CUtensorMapInterleave, CUtensorMapSwizzle,
                             CUtensorMapL2promotion, CUtensorMapFloatOOBfill);

void make_map(EncodeFn fn, CUtensorMap* m, const void* ptr, uint64_t rows, uint64_t cols, uint32_t box_rows) {
  cuuint64_t dims[2] = {cols, rows};
  cuuint64_t strides[1] = {cols * 2};
  cuuint32_t box[2] = {64, box_rows};
  cuuint32_t es[2] = {1, 1};
  fn(m, CU_TENSOR_MAP_DATA_TYPE_BFLOAT16, 2, const_cast<void*>(ptr), dims, strides, box, es, CU_TENSOR_MAP_INTERLEAVE_NONE,
     CU_TENSOR_MAP_SWIZZLE_128B, CU_TENSOR_MAP_L2_PROMOTION_L2_256B, CU_TENSOR_MAP_FLOAT_OOB_FILL_NONE);
}

void make_act_map(EncodeFn fn, CUtensorMap* m, const void* ptr, uint64_t cols) {
  cuuint64_t dims[3] = {cols, SEQ / 2, 2};
  cuuint64_t strides[2] = {cols * 4, cols * 2};
  cuuint32_t box[3] = {64, 64, 2};
  cuuint32_t es[3] = {1, 1, 1};
  fn(m, CU_TENSOR_MAP_DATA_TYPE_BFLOAT16, 3, const_cast<void*>(ptr), dims, strides, box, es, CU_TENSOR_MAP_INTERLEAVE_NONE,
     CU_TENSOR_MAP_SWIZZLE_128B, CU_TENSOR_MAP_L2_PROMOTION_L2_128B, CU_TENSOR_MAP_FLOAT_OOB_FILL_NONE);
}

}

extern "C" void kernel_launch(void* const* d_in, const int* in_sizes, int n_in, void* d_out, int out_size) {
  (void)in_sizes; (void)n_in; (void)out_size;
  EncodeFn fn = nullptr;
  cudaDriverEntryPointQueryResult qr;
  cudaGetDriverEntryPoint("cuTensorMapEncodeTiled", (void**)&fn, cudaEnableDefault, &qr);
  Params p;
  cudaGetSymbolAddress((void**)&p.s, g_s);
  p.t = make_tabs();
  make_act_map(fn, &p.x0, d_in[0], DM);
  make_act_map(fn, &p.x, p.s->x, DM);
  make_act_map(fn, &p.o, p.s->o, DM);
  make_act_map(fn, &p.h, p.s->h, FF);
  make_map(fn, &p.wqkv, d_in[1], DM, 3 * DM, 32);
  make_map(fn, &p.wo, d_in[2], DM, DM, 64);
  make_map(fn, &p.wg, d_in[4], DM, FF, 64);
  make_map(fn, &p.wu, d_in[5], DM, FF, 64);
  {
    cuuint64_t dims[5] = {DM, 2, 4, 4, FF / 32};
    cuuint64_t strides[4] = {DM * 2, DM * 16, DM * 4, DM * 64};
    cuuint32_t box[5] = {64, 2, 4, 4, 2};
    cuuint32_t es[5] = {1, 1, 1, 1, 1};
    fn(&p.wd, CU_TENSOR_MAP_DATA_TYPE_BFLOAT16, 5, d_in[6], dims, strides, box, es, CU_TENSOR_MAP_INTERLEAVE_NONE,
       CU_TENSOR_MAP_SWIZZLE_128B, CU_TENSOR_MAP_L2_PROMOTION_L2_256B, CU_TENSOR_MAP_FLOAT_OOB_FILL_NONE);
  }
  p.out = (__nv_bfloat16*)d_out;
  cudaFuncSetAttribute(fused_kernel<true>, cudaFuncAttributeMaxDynamicSharedMemorySize, SMEM_BYTES);
  cudaFuncSetAttribute(fused_kernel<false>, cudaFuncAttributeMaxDynamicSharedMemorySize, SMEM_BYTES);
  bool by_sm;
  {
    int dev = 0, sms = 0, nclusters = 0;
    cudaGetDevice(&dev);
    cudaDeviceGetAttribute(&sms, cudaDevAttrMultiProcessorCount, dev);
    cudaLaunchConfig_t cfg = {};
    cfg.gridDim = dim3(NCTA + NSPARE);
    cfg.blockDim = dim3(384);
    cfg.dynamicSmemBytes = SMEM_BYTES;
    cudaOccupancyMaxActiveClusters(&nclusters, fused_kernel<true>, &cfg);
    by_sm = sms == 132 && nclusters == 66;
  }
  if (by_sm) fused_kernel<true><<<NCTA + NSPARE, 384, SMEM_BYTES, cudaStreamPerThread>>>(p);
  else fused_kernel<false><<<NCTA + NSPARE, 384, SMEM_BYTES, cudaStreamPerThread>>>(p);
}
```
